```python
import torch

def _softmax(x, axis=-1):
    return torch.softmax(x, dim=axis)
def _gelu(x):
    return torch.nn.functional.gelu(x, approximate="tanh")
def _silu(x):
    return torch.nn.functional.silu(x)
def _sigmoid(x):
    return torch.sigmoid(x)
def _layernorm(x, axis=-1, eps=1e-5):
    m = x.mean(dim=axis, keepdim=True)
    v = x.var(dim=axis, keepdim=True, unbiased=False)
    return (x - m) / torch.sqrt(v + eps)
def _scatter_add(tgt, idx, src, axis=0):
    return tgt.clone().index_add_(axis, idx, src)
def _segment_sum(src, seg, n):
    out = torch.zeros((n,) + src.shape[1:], dtype=src.dtype)
    return out.index_add_(0, seg, src)
def _pad(x, pw):
    flat = tuple(v for pair in reversed(pw) for v in pair)
    return torch.nn.functional.pad(x, flat)

kernel_name = 'interleave_layers__mha_block__glu_gated_glu__prompt'

def setup_inputs():

    _w = (lambda a: (lambda t: t.to(torch.bfloat16) if t.is_floating_point() else t)(torch.as_tensor(a)))
    def _A_setup():
        B, S, D, H = 1, 2048, 448, 16
        return {
            "x": _w((lambda *s: torch.randn(*s, dtype=torch.bfloat16) * 0.05)(B, S, D)),
            "wqkv": _w((lambda *s: torch.randn(*s, dtype=torch.bfloat16) * 0.05)(D, 3 * D)),
            "wo": _w((lambda *s: torch.randn(*s, dtype=torch.bfloat16) * 0.05)(D, D)),
        }
    _A_in = _A_setup()

    def _B_setup():
        B, S, D, F = 1, 2048, 448, 1792
        return {
            "x": _w((lambda *s: torch.randn(*s, dtype=torch.bfloat16) * 0.05)(B, S, D)),
            "w_gate": _w((lambda *s: torch.randn(*s, dtype=torch.bfloat16) * 0.05)(D, F)),
            "w_up": _w((lambda *s: torch.randn(*s, dtype=torch.bfloat16) * 0.05)(D, F)),
            "w_down": _w((lambda *s: torch.randn(*s, dtype=torch.bfloat16) * 0.05)(F, D)),
        }
    _B_in = _B_setup()

    return {
        "A_x": _A_in["x"],
        "A_wqkv": _A_in["wqkv"],
        "A_wo": _A_in["wo"],
        "B_x": _B_in["x"],
        "B_w_gate": _B_in["w_gate"],
        "B_w_up": _B_in["w_up"],
        "B_w_down": _B_in["w_down"],
    }

def reference(A_x, A_wqkv, A_wo, B_x, B_w_gate, B_w_up, B_w_down):
    def _A_ref(x, wqkv, wo):
        B, S, D = x.shape
        H = 16
        Dh = D // H
        qkv = (lambda x, *d: x.permute(*d))((x @ wqkv).reshape(B, S, 3, H, Dh), 2, 0, 3, 1, 4)
        q, k, v = qkv[0], qkv[1], qkv[2]
        scores = torch.einsum("bhqd,bhkd->bhqk", q, k) * (Dh ** -0.5)
        p = _softmax(scores, axis=-1)
        o = torch.einsum("bhqk,bhkd->bhqd", p, v)
        return (lambda x, *d: x.permute(*d))(o, 0, 2, 1, 3).reshape(B, S, D) @ wo

    def _B_ref(x, w_gate, w_up, w_down):
        g = torch.einsum("bsd,df->bsf", x, w_gate)
        u = torch.einsum("bsd,df->bsf", x, w_up)
        h = _sigmoid(g) * u
        return torch.einsum("bsf,fd->bsd", h, w_down)

    x = A_x
    x = x + _A_ref(_layernorm(x, axis=-1), A_wqkv, A_wo)
    x = x + _B_ref(_layernorm(x, axis=-1), B_w_gate, B_w_up, B_w_down)
    x = x + _A_ref(_layernorm(x, axis=-1), A_wqkv, A_wo)
    x = x + _B_ref(_layernorm(x, axis=-1), B_w_gate, B_w_up, B_w_down)
    return x
```

```cpp
#include <cuda_runtime.h>
#include <cuda_bf16.h>
#include <cuda.h>
#include <stdint.h>

typedef __nv_bfloat16 bf16;
constexpr int S_ = 2048, D_ = 448, H_ = 16, DH_ = 28, F_ = 1792, NQ_ = 1344;

__device__ __align__(1024) bf16 g_qkv[3 * H_ * S_ * 32];
__device__ __align__(1024) bf16 g_o[S_ * D_];
__device__ __align__(1024) bf16 g_x[3][S_ * D_];
__device__ __align__(1024) bf16 g_h[16 * 56 * 128 * 32];
__device__ __align__(16) float2 g_stats[S_ * 8];
__device__ __align__(16) float g_cs[NQ_ + 2 * F_];

#define TL(k, i)

__device__ __forceinline__ uint32_t s2u(const void* p) { return (uint32_t)__cvta_generic_to_shared(p); }
__device__ __forceinline__ void mbar_init(uint32_t b, int c) { asm volatile("mbarrier.init.shared::cta.b64 [%0], %1;" ::"r"(b), "r"(c) : "memory"); }
__device__ __forceinline__ void mbar_expect(uint32_t b, uint32_t bytes) { asm volatile("mbarrier.arrive.expect_tx.shared::cta.b64 _, [%0], %1;" ::"r"(b), "r"(bytes) : "memory"); }
__device__ __forceinline__ void mbar_arrive(uint32_t b) { asm volatile("mbarrier.arrive.shared::cta.b64 _, [%0];" ::"r"(b) : "memory"); }
__device__ __forceinline__ void mbar_wait(uint32_t b, uint32_t ph) {
  uint32_t ok; int n = 0;
  do {
    asm volatile("{.reg .pred p; mbarrier.try_wait.parity.shared::cta.b64 p, [%1], %2; selp.u32 %0,1,0,p;}" : "=r"(ok) : "r"(b), "r"(ph) : "memory");
    if (++n > (1 << 24)) __trap();
  } while (!ok);
}
__device__ __forceinline__ bool elect_one() { uint32_t p; asm volatile("{.reg .pred p; elect.sync _|p, 0xffffffff; selp.u32 %0,1,0,p;}" : "=r"(p)); return p; }
__device__ __forceinline__ void tma2d(uint32_t dst, const CUtensorMap* tm, uint32_t bar, int c0, int c1) {
  asm volatile("cp.async.bulk.tensor.2d.shared::cluster.global.mbarrier::complete_tx::bytes [%0], [%1, {%3,%4}], [%2];" ::"r"(dst), "l"(tm), "r"(bar), "r"(c0), "r"(c1) : "memory");
}
__device__ __forceinline__ void tma3d(uint32_t dst, const CUtensorMap* tm, uint32_t bar, int c0, int c1, int c2) {
  asm volatile("cp.async.bulk.tensor.3d.shared::cluster.global.mbarrier::complete_tx::bytes [%0], [%1, {%3,%4,%5}], [%2];" ::"r"(dst), "l"(tm), "r"(bar), "r"(c0), "r"(c1), "r"(c2) : "memory");
}
__device__ __forceinline__ void bulk_ld(uint32_t dst, const void* src, uint32_t bytes, uint32_t bar) {
  asm volatile("cp.async.bulk.shared::cluster.global.mbarrier::complete_tx::bytes [%0], [%1], %2, [%3];" ::"r"(dst), "l"(src), "r"(bytes), "r"(bar) : "memory");
}
__device__ __forceinline__ void bulk_st(void* dst, uint32_t src, uint32_t bytes) {
  asm volatile("cp.async.bulk.global.shared::cta.bulk_group [%0], [%1], %2;" ::"l"(dst), "r"(src), "r"(bytes) : "memory");
}
__device__ __forceinline__ void bulk_commit() { asm volatile("cp.async.bulk.commit_group;" ::: "memory"); }
__device__ __forceinline__ void bulk_wait0() { asm volatile("cp.async.bulk.wait_group 0;" ::: "memory"); }
__device__ __forceinline__ void prefetch_l2(const void* p, uint32_t bytes) { asm volatile("cp.async.bulk.prefetch.L2.global [%0], %1;" ::"l"(p), "r"(bytes) : "memory"); }
__device__ __forceinline__ void prefetch_tm(const CUtensorMap* tm) { asm volatile("prefetch.tensormap [%0];" ::"l"(tm) : "memory"); }
__device__ __forceinline__ void fence_async() { asm volatile("fence.proxy.async.shared::cta;" ::: "memory"); }
__device__ __forceinline__ void fence_mbar_init() { asm volatile("fence.mbarrier_init.release.cluster;" ::: "memory"); }
__device__ __forceinline__ void pdl_launch() { asm volatile("griddepcontrol.launch_dependents;" ::: "memory"); }
__device__ __forceinline__ void pdl_wait() { asm volatile("griddepcontrol.wait;" ::: "memory"); }
__device__ __forceinline__ void named_bar(int id, int n) { asm volatile("bar.sync %0, %1;" ::"r"(id), "r"(n) : "memory"); }
__device__ __forceinline__ void wg_fence() { asm volatile("wgmma.fence.sync.aligned;" ::: "memory"); }
__device__ __forceinline__ void wg_commit() { asm volatile("wgmma.commit_group.sync.aligned;" ::: "memory"); }
template <int N> __device__ __forceinline__ void wg_wait() { asm volatile("wgmma.wait_group.sync.aligned %0;" ::"n"(N) : "memory"); }
template <int N> __device__ __forceinline__ void reg_fence(float (&d)[N]) {
#pragma unroll
  for (int i = 0; i < N; i++) asm volatile("" : "+f"(d[i])::"memory");
}
template <int N> __device__ __forceinline__ void reg_fence(uint32_t (&d)[N]) {
#pragma unroll
  for (int i = 0; i < N; i++) asm volatile("" : "+r"(d[i])::"memory");
}
__device__ __forceinline__ uint64_t mkdesc(uint32_t addr, uint32_t lbo, uint32_t sbo, uint32_t swz) {
  return (uint64_t)((addr & 0x3FFFF) >> 4) | ((uint64_t)(lbo >> 4) << 16) | ((uint64_t)(sbo >> 4) << 32) | ((uint64_t)swz << 62);
}
__device__ __forceinline__ uint32_t pack_bf16(float lo, float hi) { uint32_t r; asm("cvt.rn.bf16x2.f32 %0, %1, %2;" : "=r"(r) : "f"(hi), "f"(lo)); return r; }
__device__ __forceinline__ float bf_lo(uint32_t v) { return __uint_as_float(v << 16); }
__device__ __forceinline__ float bf_hi(uint32_t v) { return __uint_as_float(v & 0xFFFF0000u); }
__device__ __forceinline__ float ex2(float x) { float r; asm("ex2.approx.ftz.f32 %0, %1;" : "=f"(r) : "f"(x)); return r; }
__device__ __forceinline__ float rcp(float x) { float r; asm("rcp.approx.ftz.f32 %0, %1;" : "=f"(r) : "f"(x)); return r; }
__device__ __forceinline__ void sts32(uint32_t a, uint32_t v) { asm volatile("st.shared.b32 [%0], %1;" ::"r"(a), "r"(v) : "memory"); }
__device__ __forceinline__ void sts64(uint32_t a, uint32_t v0, uint32_t v1) { asm volatile("st.shared.v2.b32 [%0], {%1,%2};" ::"r"(a), "r"(v0), "r"(v1) : "memory"); }
__device__ __forceinline__ void stsm4(uint32_t a, uint32_t r0, uint32_t r1, uint32_t r2, uint32_t r3) {
  asm volatile("stmatrix.sync.aligned.m8n8.x4.shared.b16 [%0], {%1,%2,%3,%4};" ::"r"(a), "r"(r0), "r"(r1), "r"(r2), "r"(r3) : "memory");
}
__device__ __forceinline__ float2 lds64f(uint32_t a) { float2 v; asm volatile("ld.shared.v2.f32 {%0,%1}, [%2];" : "=f"(v.x), "=f"(v.y) : "r"(a) : "memory"); return v; }

template<int TB> __device__ __forceinline__ void wgmma_ss_n56(float (&d)[28], uint64_t da, uint64_t db, int sd) {
  asm volatile("{.reg .pred p; setp.ne.b32 p, %30, 0;\n"
    "wgmma.mma_async.sync.aligned.m64n56k16.f32.bf16.bf16 {%0, %1, %2, %3, %4, %5, %6, %7, %8, %9, %10, %11, %12, %13, %14, %15, %16, %17, %18, %19, %20, %21, %22, %23, %24, %25, %26, %27}, %28, %29, p, 1, 1, 0, %31;}"
    : "+f"(d[0]), "+f"(d[1]), "+f"(d[2]), "+f"(d[3]), "+f"(d[4]), "+f"(d[5]), "+f"(d[6]), "+f"(d[7]), "+f"(d[8]), "+f"(d[9]), "+f"(d[10]), "+f"(d[11]), "+f"(d[12]), "+f"(d[13]), "+f"(d[14]), "+f"(d[15]), "+f"(d[16]), "+f"(d[17]), "+f"(d[18]), "+f"(d[19]), "+f"(d[20]), "+f"(d[21]), "+f"(d[22]), "+f"(d[23]), "+f"(d[24]), "+f"(d[25]), "+f"(d[26]), "+f"(d[27])
    : "l"(da), "l"(db), "r"(sd), "n"(TB));
}
template<int TB> __device__ __forceinline__ void wgmma_ss_n64(float (&d)[32], uint64_t da, uint64_t db, int sd) {
  asm volatile("{.reg .pred p; setp.ne.b32 p, %34, 0;\n"
    "wgmma.mma_async.sync.aligned.m64n64k16.f32.bf16.bf16 {%0, %1, %2, %3, %4, %5, %6, %7, %8, %9, %10, %11, %12, %13, %14, %15, %16, %17, %18, %19, %20, %21, %22, %23, %24, %25, %26, %27, %28, %29, %30, %31}, %32, %33, p, 1, 1, 0, %35;}"
    : "+f"(d[0]), "+f"(d[1]), "+f"(d[2]), "+f"(d[3]), "+f"(d[4]), "+f"(d[5]), "+f"(d[6]), "+f"(d[7]), "+f"(d[8]), "+f"(d[9]), "+f"(d[10]), "+f"(d[11]), "+f"(d[12]), "+f"(d[13]), "+f"(d[14]), "+f"(d[15]), "+f"(d[16]), "+f"(d[17]), "+f"(d[18]), "+f"(d[19]), "+f"(d[20]), "+f"(d[21]), "+f"(d[22]), "+f"(d[23]), "+f"(d[24]), "+f"(d[25]), "+f"(d[26]), "+f"(d[27]), "+f"(d[28]), "+f"(d[29]), "+f"(d[30]), "+f"(d[31])
    : "l"(da), "l"(db), "r"(sd), "n"(TB));
}
template<int TB> __device__ __forceinline__ void wgmma_ss_n168(float (&d)[84], uint64_t da, uint64_t db, int sd) {
  asm volatile("{.reg .pred p; setp.ne.b32 p, %86, 0;\n"
    "wgmma.mma_async.sync.aligned.m64n168k16.f32.bf16.bf16 {%0, %1, %2, %3, %4, %5, %6, %7, %8, %9, %10, %11, %12, %13, %14, %15, %16, %17, %18, %19, %20, %21, %22, %23, %24, %25, %26, %27, %28, %29, %30, %31, %32, %33, %34, %35, %36, %37, %38, %39, %40, %41, %42, %43, %44, %45, %46, %47, %48, %49, %50, %51, %52, %53, %54, %55, %56, %57, %58, %59, %60, %61, %62, %63, %64, %65, %66, %67, %68, %69, %70, %71, %72, %73, %74, %75, %76, %77, %78, %79, %80, %81, %82, %83}, %84, %85, p, 1, 1, 0, %87;}"
    : "+f"(d[0]), "+f"(d[1]), "+f"(d[2]), "+f"(d[3]), "+f"(d[4]), "+f"(d[5]), "+f"(d[6]), "+f"(d[7]), "+f"(d[8]), "+f"(d[9]), "+f"(d[10]), "+f"(d[11]), "+f"(d[12]), "+f"(d[13]), "+f"(d[14]), "+f"(d[15]), "+f"(d[16]), "+f"(d[17]), "+f"(d[18]), "+f"(d[19]), "+f"(d[20]), "+f"(d[21]), "+f"(d[22]), "+f"(d[23]), "+f"(d[24]), "+f"(d[25]), "+f"(d[26]), "+f"(d[27]), "+f"(d[28]), "+f"(d[29]), "+f"(d[30]), "+f"(d[31]), "+f"(d[32]), "+f"(d[33]), "+f"(d[34]), "+f"(d[35]), "+f"(d[36]), "+f"(d[37]), "+f"(d[38]), "+f"(d[39]), "+f"(d[40]), "+f"(d[41]), "+f"(d[42]), "+f"(d[43]), "+f"(d[44]), "+f"(d[45]), "+f"(d[46]), "+f"(d[47]), "+f"(d[48]), "+f"(d[49]), "+f"(d[50]), "+f"(d[51]), "+f"(d[52]), "+f"(d[53]), "+f"(d[54]), "+f"(d[55]), "+f"(d[56]), "+f"(d[57]), "+f"(d[58]), "+f"(d[59]), "+f"(d[60]), "+f"(d[61]), "+f"(d[62]), "+f"(d[63]), "+f"(d[64]), "+f"(d[65]), "+f"(d[66]), "+f"(d[67]), "+f"(d[68]), "+f"(d[69]), "+f"(d[70]), "+f"(d[71]), "+f"(d[72]), "+f"(d[73]), "+f"(d[74]), "+f"(d[75]), "+f"(d[76]), "+f"(d[77]), "+f"(d[78]), "+f"(d[79]), "+f"(d[80]), "+f"(d[81]), "+f"(d[82]), "+f"(d[83])
    : "l"(da), "l"(db), "r"(sd), "n"(TB));
}
template<int TB> __device__ __forceinline__ void wgmma_ss_n224(float (&d)[112], uint64_t da, uint64_t db, int sd) {
  asm volatile("{.reg .pred p; setp.ne.b32 p, %114, 0;\n"
    "wgmma.mma_async.sync.aligned.m64n224k16.f32.bf16.bf16 {%0, %1, %2, %3, %4, %5, %6, %7, %8, %9, %10, %11, %12, %13, %14, %15, %16, %17, %18, %19, %20, %21, %22, %23, %24, %25, %26, %27, %28, %29, %30, %31, %32, %33, %34, %35, %36, %37, %38, %39, %40, %41, %42, %43, %44, %45, %46, %47, %48, %49, %50, %51, %52, %53, %54, %55, %56, %57, %58, %59, %60, %61, %62, %63, %64, %65, %66, %67, %68, %69, %70, %71, %72, %73, %74, %75, %76, %77, %78, %79, %80, %81, %82, %83, %84, %85, %86, %87, %88, %89, %90, %91, %92, %93, %94, %95, %96, %97, %98, %99, %100, %101, %102, %103, %104, %105, %106, %107, %108, %109, %110, %111}, %112, %113, p, 1, 1, 0, %115;}"
    : "+f"(d[0]), "+f"(d[1]), "+f"(d[2]), "+f"(d[3]), "+f"(d[4]), "+f"(d[5]), "+f"(d[6]), "+f"(d[7]), "+f"(d[8]), "+f"(d[9]), "+f"(d[10]), "+f"(d[11]), "+f"(d[12]), "+f"(d[13]), "+f"(d[14]), "+f"(d[15]), "+f"(d[16]), "+f"(d[17]), "+f"(d[18]), "+f"(d[19]), "+f"(d[20]), "+f"(d[21]), "+f"(d[22]), "+f"(d[23]), "+f"(d[24]), "+f"(d[25]), "+f"(d[26]), "+f"(d[27]), "+f"(d[28]), "+f"(d[29]), "+f"(d[30]), "+f"(d[31]), "+f"(d[32]), "+f"(d[33]), "+f"(d[34]), "+f"(d[35]), "+f"(d[36]), "+f"(d[37]), "+f"(d[38]), "+f"(d[39]), "+f"(d[40]), "+f"(d[41]), "+f"(d[42]), "+f"(d[43]), "+f"(d[44]), "+f"(d[45]), "+f"(d[46]), "+f"(d[47]), "+f"(d[48]), "+f"(d[49]), "+f"(d[50]), "+f"(d[51]), "+f"(d[52]), "+f"(d[53]), "+f"(d[54]), "+f"(d[55]), "+f"(d[56]), "+f"(d[57]), "+f"(d[58]), "+f"(d[59]), "+f"(d[60]), "+f"(d[61]), "+f"(d[62]), "+f"(d[63]), "+f"(d[64]), "+f"(d[65]), "+f"(d[66]), "+f"(d[67]), "+f"(d[68]), "+f"(d[69]), "+f"(d[70]), "+f"(d[71]), "+f"(d[72]), "+f"(d[73]), "+f"(d[74]), "+f"(d[75]), "+f"(d[76]), "+f"(d[77]), "+f"(d[78]), "+f"(d[79]), "+f"(d[80]), "+f"(d[81]), "+f"(d[82]), "+f"(d[83]), "+f"(d[84]), "+f"(d[85]), "+f"(d[86]), "+f"(d[87]), "+f"(d[88]), "+f"(d[89]), "+f"(d[90]), "+f"(d[91]), "+f"(d[92]), "+f"(d[93]), "+f"(d[94]), "+f"(d[95]), "+f"(d[96]), "+f"(d[97]), "+f"(d[98]), "+f"(d[99]), "+f"(d[100]), "+f"(d[101]), "+f"(d[102]), "+f"(d[103]), "+f"(d[104]), "+f"(d[105]), "+f"(d[106]), "+f"(d[107]), "+f"(d[108]), "+f"(d[109]), "+f"(d[110]), "+f"(d[111])
    : "l"(da), "l"(db), "r"(sd), "n"(TB));
}
template<int TB> __device__ __forceinline__ void wgmma_rs_n32(float (&d)[16], uint32_t a0, uint32_t a1, uint32_t a2, uint32_t a3, uint64_t db, int sd) {
  asm volatile("{.reg .pred p; setp.ne.b32 p, %21, 0;\n"
    "wgmma.mma_async.sync.aligned.m64n32k16.f32.bf16.bf16 {%0, %1, %2, %3, %4, %5, %6, %7, %8, %9, %10, %11, %12, %13, %14, %15}, {%16, %17, %18, %19}, %20, p, 1, 1, %22;}"
    : "+f"(d[0]), "+f"(d[1]), "+f"(d[2]), "+f"(d[3]), "+f"(d[4]), "+f"(d[5]), "+f"(d[6]), "+f"(d[7]), "+f"(d[8]), "+f"(d[9]), "+f"(d[10]), "+f"(d[11]), "+f"(d[12]), "+f"(d[13]), "+f"(d[14]), "+f"(d[15])
    : "r"(a0), "r"(a1), "r"(a2), "r"(a3), "l"(db), "r"(sd), "n"(TB));
}
template<int TB> __device__ __forceinline__ void wgmma_rs_n64(float (&d)[32], uint32_t a0, uint32_t a1, uint32_t a2, uint32_t a3, uint64_t db, int sd) {
  asm volatile("{.reg .pred p; setp.ne.b32 p, %37, 0;\n"
    "wgmma.mma_async.sync.aligned.m64n64k16.f32.bf16.bf16 {%0, %1, %2, %3, %4, %5, %6, %7, %8, %9, %10, %11, %12, %13, %14, %15, %16, %17, %18, %19, %20, %21, %22, %23, %24, %25, %26, %27, %28, %29, %30, %31}, {%32, %33, %34, %35}, %36, p, 1, 1, %38;}"
    : "+f"(d[0]), "+f"(d[1]), "+f"(d[2]), "+f"(d[3]), "+f"(d[4]), "+f"(d[5]), "+f"(d[6]), "+f"(d[7]), "+f"(d[8]), "+f"(d[9]), "+f"(d[10]), "+f"(d[11]), "+f"(d[12]), "+f"(d[13]), "+f"(d[14]), "+f"(d[15]), "+f"(d[16]), "+f"(d[17]), "+f"(d[18]), "+f"(d[19]), "+f"(d[20]), "+f"(d[21]), "+f"(d[22]), "+f"(d[23]), "+f"(d[24]), "+f"(d[25]), "+f"(d[26]), "+f"(d[27]), "+f"(d[28]), "+f"(d[29]), "+f"(d[30]), "+f"(d[31])
    : "r"(a0), "r"(a1), "r"(a2), "r"(a3), "l"(db), "r"(sd), "n"(TB));
}

__device__ __forceinline__ float2 row_stats(int row) {
  const float4* p = reinterpret_cast<const float4*>(g_stats + row * 8);
  float4 a = __ldcg(p), b = __ldcg(p + 1), c = __ldcg(p + 2), d = __ldcg(p + 3);
  float mean = (((a.x + a.z) + (b.x + b.z)) + ((c.x + c.z) + (d.x + d.z))) * (1.0f / D_);
  float m2 = ((a.y + a.w) + (b.y + b.w)) + ((c.y + c.w) + (d.y + d.w));
  const float i56 = 1.0f / 56.0f;
  float e, acc = 0.f;
  e = a.x * i56 - mean; acc += e * e;  e = a.z * i56 - mean; acc += e * e;
  e = b.x * i56 - mean; acc += e * e;  e = b.z * i56 - mean; acc += e * e;
  e = c.x * i56 - mean; acc += e * e;  e = c.z * i56 - mean; acc += e * e;
  e = d.x * i56 - mean; acc += e * e;  e = d.z * i56 - mean; acc += e * e;
  float var = (m2 + 56.0f * acc) * (1.0f / D_);
  return make_float2(mean, rsqrtf(var + 1e-5f));
}

__global__ void __launch_bounds__(256) k0_prep(const bf16* __restrict__ x, const bf16* __restrict__ wqkv, const bf16* __restrict__ wg,
                                               const bf16* __restrict__ wu, const bf16* __restrict__ wo, const bf16* __restrict__ wd) {
  pdl_launch();
  TL(0, 0);
  __shared__ float red[32][65];
  int b = blockIdx.x, tid = threadIdx.x;
  if (b < 64) {
    int lane = tid & 31, w = tid >> 5;
#pragma unroll
    for (int i = 0; i < 4; i++) {
      int row = b * 32 + w * 4 + i;
      const uint32_t* p = reinterpret_cast<const uint32_t*>(x + row * D_ + lane * 14);
      uint32_t v[7]; float s = 0.f;
#pragma unroll
      for (int k = 0; k < 7; k++) v[k] = __ldg(p + k);
#pragma unroll
      for (int k = 0; k < 7; k++) s += bf_lo(v[k]) + bf_hi(v[k]);
      s += __shfl_xor_sync(~0u, s, 1); s += __shfl_xor_sync(~0u, s, 2);
      float mu = s * (1.0f / 56.0f), m2 = 0.f;
#pragma unroll
      for (int k = 0; k < 7; k++) { float e0 = bf_lo(v[k]) - mu, e1 = bf_hi(v[k]) - mu; m2 += e0 * e0 + e1 * e1; }
      m2 += __shfl_xor_sync(~0u, m2, 1); m2 += __shfl_xor_sync(~0u, m2, 2);
      if ((lane & 3) == 0) g_stats[row * 8 + (lane >> 2)] = make_float2(s, m2);
    }
  } else {
    int cb = b - 64;
    const bf16* w; int ld, c0;
    if (cb < 21) { w = wqkv; ld = NQ_; c0 = cb * 64; }
    else if (cb < 49) { w = wg; ld = F_; c0 = (cb - 21) * 64; }
    else { w = wu; ld = F_; c0 = (cb - 49) * 64; }
    int rg = tid >> 3, cg = tid & 7;
    uint4 v[14];
#pragma unroll
    for (int i = 0; i < 14; i++) v[i] = __ldg(reinterpret_cast<const uint4*>(w + (size_t)(rg + 32 * i) * ld + c0 + cg * 8));
    float a[8] = {0, 0, 0, 0, 0, 0, 0, 0};
#pragma unroll
    for (int i = 0; i < 14; i++) {
      a[0] += bf_lo(v[i].x); a[1] += bf_hi(v[i].x); a[2] += bf_lo(v[i].y); a[3] += bf_hi(v[i].y);
      a[4] += bf_lo(v[i].z); a[5] += bf_hi(v[i].z); a[6] += bf_lo(v[i].w); a[7] += bf_hi(v[i].w);
    }
#pragma unroll
    for (int i = 0; i < 8; i++) red[rg][cg * 8 + i] = a[i];
    __syncthreads();
    if (tid < 64) {
      float s = 0.f;
#pragma unroll
      for (int i = 0; i < 32; i++) s += red[i][tid];
      g_cs[cb * 64 + tid] = s;
    }
    if (tid == 64) {
      if (cb < 64) prefetch_l2(reinterpret_cast<const char*>(wd) + cb * 25088, 25088);
      else if (cb < 72) prefetch_l2(reinterpret_cast<const char*>(wo) + (cb - 64) * 50176, 50176);
    }
  }
  TL(0, 3);
}

constexpr int K1_ST = 5, K1_STAGE = 16384 + 24576;
constexpr int K1_SMEM = K1_ST * K1_STAGE + 2048 + 1024;
__global__ void __launch_bounds__(288) k1_qkv(const __grid_constant__ CUtensorMap tmA, const __grid_constant__ CUtensorMap tmB, int first, int kid) {
  extern __shared__ uint8_t smem_raw[];
  uint32_t sm = (s2u(smem_raw) + 1023) & ~1023u;
  asm volatile("" : "+r"(sm));
  const uint32_t aux = sm + K1_ST * K1_STAGE;
  const uint32_t bars = aux + 1792;
  const int tid = threadIdx.x, warp = tid >> 5, lane = tid & 31;
  const int tb = blockIdx.x >> 3, j = blockIdx.x & 7;
  pdl_launch();
  if (tid == 0) TL(kid, 0);
  if (tid == 0) {
    for (int i = 0; i < K1_ST; i++) { mbar_init(bars + i * 8, 1); mbar_init(bars + 64 + i * 8, 2); }
    fence_mbar_init();
    prefetch_tm(&tmA); prefetch_tm(&tmB);
  }
  __syncthreads();
  if (warp == 8) {
    const bool e = elect_one();
    if (e) {
#pragma unroll
      for (int s = 0; s < K1_ST; s++) {
        mbar_expect(bars + s * 8, K1_STAGE);
#pragma unroll
        for (int q = 0; q < 3; q++) tma2d(sm + s * K1_STAGE + 16384 + q * 8192, &tmB, bars + s * 8, j * 168 + q * 64, s * 64);
        if (first) tma2d(sm + s * K1_STAGE, &tmA, bars + s * 8, s * 64, tb * 128);
      }
    }
    if (!first) {
      pdl_wait();
      if (e) {
#pragma unroll
        for (int s = 0; s < K1_ST; s++) tma2d(sm + s * K1_STAGE, &tmA, bars + s * 8, s * 64, tb * 128);
      }
    }
#pragma unroll
    for (int kc = K1_ST; kc < 7; kc++) {
      const int s = kc - K1_ST;
      mbar_wait(bars + 64 + s * 8, 0);
      if (e) {
        mbar_expect(bars + s * 8, K1_STAGE);
        tma2d(sm + s * K1_STAGE, &tmA, bars + s * 8, kc * 64, tb * 128);
#pragma unroll
        for (int q = 0; q < 3; q++) tma2d(sm + s * K1_STAGE + 16384 + q * 8192, &tmB, bars + s * 8, j * 168 + q * 64, kc * 64);
      }
    }
    pdl_wait();
    if (lane == 0) TL(kid, 1);
#pragma unroll
    for (int i = 0; i < 4; i++) {
      float2 st = row_stats(tb * 128 + i * 32 + lane);
      sts64(aux + (i * 32 + lane) * 8, __float_as_uint(st.x), __float_as_uint(st.y));
    }
    for (int i = lane; i < 168; i += 32) sts32(aux + 1024 + i * 4, __float_as_uint(__ldcg(g_cs + j * 168 + i)));
    named_bar(1, 288);
  } else {
    const int wg = warp >> 2;
    float acc[84];
#pragma unroll
    for (int i = 0; i < 84; i++) acc[i] = 0.f;
#pragma unroll
    for (int kc = 0; kc < 7; kc++) {
      const int s = kc % K1_ST;
      mbar_wait(bars + s * 8, kc / K1_ST);
      const uint32_t a0 = sm + s * K1_STAGE + wg * 8192, b0 = sm + s * K1_STAGE + 16384;
      wg_fence();
#pragma unroll
      for (int k = 0; k < 4; k++) wgmma_ss_n168<1>(acc, mkdesc(a0 + k * 32, 16, 1024, 1), mkdesc(b0 + k * 2048, 8192, 1024, 1), 1);
      wg_commit();
      if (kc > 0 && kc - 1 + K1_ST < 7) {
        wg_wait<1>();
        if ((tid & 127) == 0) mbar_arrive(bars + 64 + (kc - 1) * 8);
      }
    }
    wg_wait<0>();
    reg_fence(acc);
    if (tid == 0) TL(kid, 2);
    named_bar(1, 288);
    const int g = lane >> 2, t = lane & 3;
    const int r0 = wg * 64 + (warp & 3) * 16 + g;
    const float2 st0 = lds64f(aux + r0 * 8), st1 = lds64f(aux + (r0 + 8) * 8);
    const float qs = 0.18898223650461362f * 1.4426950408889634f;
    const uint32_t sw = (g >> 1) & 3;
#pragma unroll
    for (int c = 0; c < 21; c++) {
      const int n = c * 8 + 2 * t;
      const int hp = n / 28, d = n - hp * 28;
      const float sc = (j * 6 + hp < 16) ? qs : 1.0f;
      const float2 cs = lds64f(aux + 1024 + n * 4);
      const float s0 = st0.y * sc, s1 = st1.y * sc;
      const uint32_t v0 = pack_bf16((acc[4 * c] - st0.x * cs.x) * s0, (acc[4 * c + 1] - st0.x * cs.y) * s0);
      const uint32_t v1 = pack_bf16((acc[4 * c + 2] - st1.x * cs.x) * s1, (acc[4 * c + 3] - st1.x * cs.y) * s1);
      const uint32_t a = sm + hp * 8192 + r0 * 64 + ((((uint32_t)d >> 3) ^ sw) << 4) + (d & 7) * 2;
      sts32(a, v0); sts32(a + 512, v1);
    }
    for (int i = tid & 127; i < 6 * 64; i += 128) {
      const int hp = i >> 6, r = wg * 64 + (i & 63);
      sts64(sm + hp * 8192 + r * 64 + ((3u ^ ((r >> 1) & 3)) << 4) + 8, (j * 6 + hp < 16) ? 0u : 0x3F80u, 0u);
    }
    fence_async();
    named_bar(2 + wg, 128);
    if ((tid & 127) < 6) {
      const int hp = tid & 127;
      bulk_st(g_qkv + ((size_t)(j * 6 + hp) * S_ + tb * 128 + wg * 64) * 32, sm + hp * 8192 + wg * 4096, 4096);
      bulk_commit(); bulk_wait0();
    }
    if (tid == 0) TL(kid, 3);
  }
}

constexpr int K2_ST = 12, K2_STAGE = 16384;
constexpr int K2_SMEM = K2_ST * K2_STAGE + 16384 + 1024 + 256;

__device__ __forceinline__ void qk64(float (&s)[32], uint32_t qaddr, const uint32_t (&q)[4], uint32_t kaddr) {
  wg_fence();
  wgmma_ss_n64<0>(s, mkdesc(qaddr, 16, 512, 2), mkdesc(kaddr, 16, 512, 2), qaddr & 1);
  wgmma_rs_n64<0>(s, q[0], q[1], q[2], q[3], mkdesc(kaddr + 32, 16, 512, 2), 1);
  wg_commit();
}
__device__ __forceinline__ void pv64(float (&o)[16], const uint32_t (&p)[16], uint32_t vaddr) {
  wg_fence();
#pragma unroll
  for (int k = 0; k < 4; k++) wgmma_rs_n32<1>(o, p[4 * k], p[4 * k + 1], p[4 * k + 2], p[4 * k + 3], mkdesc(vaddr + k * 1024, 16, 512, 2), 1);
  wg_commit();
}
__device__ __forceinline__ void softmax_fast(const float (&s)[32], uint32_t (&p)[16]) {
#pragma unroll
  for (int i = 0; i < 16; i++) p[i] = pack_bf16(ex2(s[2 * i]), ex2(s[2 * i + 1]));
  reg_fence(p);
}
__device__ __forceinline__ void rowmax64(const float (&s)[32], float& m0, float& m1) {
  m0 = fmaxf(s[0], s[1]); m1 = fmaxf(s[2], s[3]);
#pragma unroll
  for (int c = 1; c < 8; c++) { m0 = fmaxf(m0, fmaxf(s[4 * c], s[4 * c + 1])); m1 = fmaxf(m1, fmaxf(s[4 * c + 2], s[4 * c + 3])); }
  m0 = fmaxf(m0, __shfl_xor_sync(~0u, m0, 1)); m0 = fmaxf(m0, __shfl_xor_sync(~0u, m0, 2));
  m1 = fmaxf(m1, __shfl_xor_sync(~0u, m1, 1)); m1 = fmaxf(m1, __shfl_xor_sync(~0u, m1, 2));
}

__device__ __forceinline__ void kv_load(uint32_t sm, uint32_t bars, const bf16* kg, int blk, int s) {
  mbar_expect(bars + s * 8, K2_STAGE);
  bulk_ld(sm + s * K2_STAGE, kg + blk * 4096, 8192, bars + s * 8);
  bulk_ld(sm + s * K2_STAGE + 8192, kg + (size_t)16 * S_ * 32 + blk * 4096, 8192, bars + s * 8);
}

__global__ void __launch_bounds__(512, 1) k2_attn(int kid) {
  extern __shared__ uint8_t smem_raw[];
  uint32_t sm = (s2u(smem_raw) + 1023) & ~1023u;
  asm volatile("" : "+r"(sm));
  const uint32_t bars = sm + K2_ST * K2_STAGE + 16384;
  const int tid = threadIdx.x, warp = tid >> 5, lane = tid & 31;
  const int h = blockIdx.x >> 3, qb = blockIdx.x & 7;
  pdl_launch();
  if (tid == 0) TL(kid, 0);
  if (tid == 0) {
    for (int i = 0; i < K2_ST; i++) mbar_init(bars + i * 8, 1);
    for (int i = 0; i < 4; i++) mbar_init(bars + 128 + i * 8, 4);
    mbar_init(bars + 192, 1);
    fence_mbar_init();
  }
  __syncthreads();
  pdl_wait();
  if (tid == 0) TL(kid, 1);
  const bf16* kg = g_qkv + (size_t)(16 + h) * S_ * 32;
  if (tid == 0) {
    mbar_expect(bars + 192, 16384);
    bulk_ld(sm + K2_ST * K2_STAGE, g_qkv + ((size_t)h * S_ + qb * 256) * 32, 16384, bars + 192);
#pragma unroll 1
    for (int i = 0; i < K2_ST; i++) kv_load(sm, bars, kg, i, i);
  }
  const int wg = warp >> 2, g = lane >> 2, t = lane & 3;
  const int row = qb * 256 + wg * 64 + (warp & 3) * 16 + g;
  uint32_t q[4];
  {
    const uint32_t* qp = reinterpret_cast<const uint32_t*>(g_qkv + ((size_t)h * S_ + row) * 32);
    const int sw = (row >> 1) & 3;
#pragma unroll
    for (int c = 2; c < 4; c++) {
      q[(c & 1) * 2] = __ldcg(qp + ((c ^ sw) << 2) + t);
      q[(c & 1) * 2 + 1] = __ldcg(qp + 128 + ((c ^ sw) << 2) + t);
    }
  }
  const uint32_t qa = sm + K2_ST * K2_STAGE + wg * 4096;
  float o[16], sa[32];
  uint32_t p[16], p2[16];
#pragma unroll
  for (int i = 0; i < 16; i++) o[i] = 0.f;
#pragma unroll
  for (int i = 0; i < 32; i++) sa[i] = 0.f;
  reg_fence(o); reg_fence(sa);
  mbar_wait(bars + 192, 0);
  mbar_wait(bars, 0);
  qk64(sa, qa, q, sm);
  wg_wait<0>();
  reg_fence(sa);
  {
    float m0, m1;
    rowmax64(sa, m0, m1);
    if (t == 2) { q[2] = pack_bf16(-m0, 0.f); q[3] = pack_bf16(-m1, 0.f); }
    reg_fence(q);
  }
  qk64(sa, qa, q, sm);
  wg_wait<0>();
#pragma unroll 1
  for (int i = 0; i < 16; i++) {
    const int s = i < K2_ST ? i : i - K2_ST;
    const uint32_t kb = sm + s * K2_STAGE, vb = kb + 8192;
    reg_fence(sa);
    softmax_fast(sa, p);
    qk64(sa, qa, q, kb + 4096);
    pv64(o, p, vb);
    const int s2 = i + 1 < K2_ST ? i + 1 : i + 1 - K2_ST;
    if (i < 15) mbar_wait(bars + s2 * 8, i + 1 < K2_ST ? 0 : 1);
    wg_wait<1>();
    reg_fence(sa);
    if (i >= 1 && i <= 4 && (tid & 127) == 0) mbar_arrive(bars + 128 + (i - 1) * 8);
    if (i >= 4 && i < 8 && tid == 0) { mbar_wait(bars + 128 + (i - 4) * 8, 0); kv_load(sm, bars, kg, K2_ST + i - 4, i - 4); }
    softmax_fast(sa, p2);
    qk64(sa, qa, q, sm + s2 * K2_STAGE);
    pv64(o, p2, vb + 4096);
    wg_wait<1>();
  }
  wg_wait<0>();
  reg_fence(o);
  if (tid == 0) TL(kid, 2);
  float l0 = __shfl_sync(~0u, o[12], (lane & ~3) | 2), l1 = __shfl_sync(~0u, o[14], (lane & ~3) | 2);
  bool bad = !(l0 < 134217728.f) || !(l1 < 134217728.f);
#pragma unroll
  for (int i = 0; i < 16; i++) bad = bad || !(fabsf(o[i]) < 3.0e38f);
  if (__syncthreads_or(bad)) {
    if (t == 2) { q[2] = 0u; q[3] = 0u; }
    float m0 = -INFINITY, m1 = -INFINITY;
#pragma unroll
    for (int i = 0; i < 16; i++) o[i] = 0.f;
#pragma unroll 1
    for (int i2 = 0; i2 < 32; i2++) {
      if ((i2 & 1) == 0) {
        __syncthreads();
        if (tid == 0) kv_load(sm, bars, kg, i2 >> 1, 0);
        mbar_wait(bars, (i2 >> 1) & 1);
      }
      const uint32_t kb = sm + (i2 & 1) * 4096;
      qk64(sa, qa, q, kb);
      wg_wait<0>();
      reg_fence(sa);
      float n0, n1;
      rowmax64(sa, n0, n1);
      n0 = fmaxf(n0, m0); n1 = fmaxf(n1, m1);
      const float c0 = ex2(m0 - n0), c1 = ex2(m1 - n1);
      m0 = n0; m1 = n1;
#pragma unroll
      for (int c = 0; c < 4; c++) { o[4 * c] *= c0; o[4 * c + 1] *= c0; o[4 * c + 2] *= c1; o[4 * c + 3] *= c1; }
#pragma unroll
      for (int c = 0; c < 8; c++) {
        p[2 * c] = pack_bf16(ex2(sa[4 * c] - m0), ex2(sa[4 * c + 1] - m0));
        p[2 * c + 1] = pack_bf16(ex2(sa[4 * c + 2] - m1), ex2(sa[4 * c + 3] - m1));
      }
      pv64(o, p, kb + 8192);
      wg_wait<0>();
      reg_fence(o);
    }
    l0 = __shfl_sync(~0u, o[12], (lane & ~3) | 2); l1 = __shfl_sync(~0u, o[14], (lane & ~3) | 2);
  }
  const float i0 = 1.0f / l0, i1 = 1.0f / l1;
  uint32_t* op = reinterpret_cast<uint32_t*>(g_o + (size_t)row * D_ + h * DH_) + t;
#pragma unroll
  for (int c = 0; c < 4; c++) {
    if (c < 3 || t < 2) {
      op[c * 4] = pack_bf16(o[4 * c] * i0, o[4 * c + 1] * i0);
      op[c * 4 + 8 * (D_ / 2)] = pack_bf16(o[4 * c + 2] * i1, o[4 * c + 3] * i1);
    }
  }
  if (tid == 0) TL(kid, 3);
}

constexpr int K3_ST = 8, K3_STAGE = 16384 + 8192;
constexpr int K3_SMEM = K3_ST * K3_STAGE + 1024 + 256;
template <int NKC, bool AH>
__global__ void __launch_bounds__(288) k3_proj(const __grid_constant__ CUtensorMap tmA, const __grid_constant__ CUtensorMap tmB,
                                               const bf16* __restrict__ resid, bf16* __restrict__ out, int kid) {
  extern __shared__ uint8_t smem_raw[];
  uint32_t sm = (s2u(smem_raw) + 1023) & ~1023u;
  asm volatile("" : "+r"(sm));
  const uint32_t bars = sm + K3_ST * K3_STAGE;
  const int tid = threadIdx.x, warp = tid >> 5, lane = tid & 31;
  const int tb = blockIdx.x >> 3, j = blockIdx.x & 7;
  constexpr int NPRE = NKC < K3_ST ? NKC : K3_ST;
  pdl_launch();
  if (tid == 0) TL(kid, 0);
  if (tid == 0) {
    for (int i = 0; i < K3_ST; i++) { mbar_init(bars + i * 8, 1); mbar_init(bars + 64 + i * 8, 2); }
    fence_mbar_init();
    prefetch_tm(&tmA); prefetch_tm(&tmB);
  }
  __syncthreads();
  if (warp == 8) {
    const bool e = elect_one();
    const bf16* hsrc = g_h + (size_t)tb * 56 * 4096;
    if (e) {
#pragma unroll
      for (int s = 0; s < NPRE; s++) {
        mbar_expect(bars + s * 8, K3_STAGE);
        tma2d(sm + s * K3_STAGE + 16384, &tmB, bars + s * 8, j * 56, s * 64);
      }
    }
    pdl_wait();
    if (lane == 0) TL(kid, 1);
    if (e) {
#pragma unroll
      for (int s = 0; s < NPRE; s++) {
        if (AH) bulk_ld(sm + s * K3_STAGE, hsrc + s * 8192, 16384, bars + s * 8);
        else tma2d(sm + s * K3_STAGE, &tmA, bars + s * 8, s * 64, tb * 128);
      }
    }
#pragma unroll 1
    for (int kc = NPRE; kc < NKC; kc++) {
      const int s = kc & (K3_ST - 1);
      mbar_wait(bars + 64 + s * 8, ((kc / K3_ST) - 1) & 1);
      if (e) {
        mbar_expect(bars + s * 8, K3_STAGE);
        if (AH) bulk_ld(sm + s * K3_STAGE, hsrc + kc * 8192, 16384, bars + s * 8);
        else tma2d(sm + s * K3_STAGE, &tmA, bars + s * 8, kc * 64, tb * 128);
        tma2d(sm + s * K3_STAGE + 16384, &tmB, bars + s * 8, j * 56, kc * 64);
      }
    }
  } else {
    const int wg = warp >> 2, g = lane >> 2, t = lane & 3;
    const int row = tb * 128 + wg * 64 + (warp & 3) * 16 + g;
    pdl_wait();
    uint32_t rs[14];
    {
      const uint32_t* rp = reinterpret_cast<const uint32_t*>(resid + (size_t)row * D_ + j * 56) + t;
#pragma unroll
      for (int c = 0; c < 7; c++) { rs[2 * c] = __ldcg(rp + c * 4); rs[2 * c + 1] = __ldcg(rp + c * 4 + 8 * (D_ / 2)); }
    }
    float acc[28];
#pragma unroll
    for (int i = 0; i < 28; i++) acc[i] = 0.f;
#pragma unroll 1
    for (int kc = 0; kc < NKC; kc++) {
      const int s = kc & (K3_ST - 1);
      mbar_wait(bars + s * 8, (kc / K3_ST) & 1);
      const uint32_t a0 = sm + s * K3_STAGE, b0 = a0 + 16384;
      wg_fence();
#pragma unroll
      for (int k = 0; k < 4; k++) {
        const uint64_t da = AH ? mkdesc(a0 + (k >> 1) * 8192 + wg * 4096 + (k & 1) * 32, 16, 512, 2) : mkdesc(a0 + wg * 8192 + k * 32, 16, 1024, 1);
        wgmma_ss_n56<1>(acc, da, mkdesc(b0 + k * 2048, 8192, 1024, 1), 1);
      }
      wg_commit();
      if (NKC > K3_ST) {
        wg_wait<1>();
        if (kc > 0 && (tid & 127) == 0) mbar_arrive(bars + 64 + ((kc - 1) & (K3_ST - 1)) * 8);
      }
    }
    wg_wait<0>();
    reg_fence(acc);
    if (tid == 0) TL(kid, 2);
    uint32_t* op = reinterpret_cast<uint32_t*>(out + (size_t)row * D_ + j * 56) + t;
    float s0 = 0.f, s1 = 0.f;
#pragma unroll
    for (int c = 0; c < 7; c++) {
      rs[2 * c] = pack_bf16(acc[4 * c] + bf_lo(rs[2 * c]), acc[4 * c + 1] + bf_hi(rs[2 * c]));
      rs[2 * c + 1] = pack_bf16(acc[4 * c + 2] + bf_lo(rs[2 * c + 1]), acc[4 * c + 3] + bf_hi(rs[2 * c + 1]));
      op[c * 4] = rs[2 * c]; op[c * 4 + 8 * (D_ / 2)] = rs[2 * c + 1];
      s0 += bf_lo(rs[2 * c]) + bf_hi(rs[2 * c]); s1 += bf_lo(rs[2 * c + 1]) + bf_hi(rs[2 * c + 1]);
    }
    s0 += __shfl_xor_sync(~0u, s0, 1); s0 += __shfl_xor_sync(~0u, s0, 2);
    s1 += __shfl_xor_sync(~0u, s1, 1); s1 += __shfl_xor_sync(~0u, s1, 2);
    const float u0 = s0 * (1.0f / 56.0f), u1 = s1 * (1.0f / 56.0f);
    float q0 = 0.f, q1 = 0.f;
#pragma unroll
    for (int c = 0; c < 7; c++) {
      float e;
      e = bf_lo(rs[2 * c]) - u0; q0 += e * e; e = bf_hi(rs[2 * c]) - u0; q0 += e * e;
      e = bf_lo(rs[2 * c + 1]) - u1; q1 += e * e; e = bf_hi(rs[2 * c + 1]) - u1; q1 += e * e;
    }
    q0 += __shfl_xor_sync(~0u, q0, 1); q0 += __shfl_xor_sync(~0u, q0, 2);
    q1 += __shfl_xor_sync(~0u, q1, 1); q1 += __shfl_xor_sync(~0u, q1, 2);
    if (t == 0) { g_stats[row * 8 + j] = make_float2(s0, q0); g_stats[(row + 8) * 8 + j] = make_float2(s1, q1); }
    if (tid == 0) TL(kid, 3);
  }
}

constexpr int K4_ST = 3, K4_BST = 28672, K4_A = 7 * 16384;
constexpr int K4_SMEM = K4_A + K4_ST * K4_BST + 4096 + 1024;
__global__ void __launch_bounds__(256, 1) k4_glu(const __grid_constant__ CUtensorMap tmA, const __grid_constant__ CUtensorMap tmG,
                                                 const __grid_constant__ CUtensorMap tmU, int kid) {
  extern __shared__ uint8_t smem_raw[];
  uint32_t sm = (s2u(smem_raw) + 1023) & ~1023u;
  asm volatile("" : "+r"(sm));
  const uint32_t sb = sm + K4_A;
  const uint32_t aux = sb + K4_ST * K4_BST;
  const uint32_t bars = aux + 3072;
  const int tid = threadIdx.x, warp = tid >> 5, lane = tid & 31;
  const int tb = blockIdx.x >> 3, j = blockIdx.x & 7;
  pdl_launch();
  if (tid == 0) TL(kid, 0);
  if (tid == 0) {
    for (int i = 0; i < 7; i++) mbar_init(bars + i * 8, 1);
    for (int i = 0; i < K4_ST; i++) { mbar_init(bars + 64 + i * 8, 1); mbar_init(bars + 96 + i * 8, 2); }
    fence_mbar_init();
#pragma unroll
    for (int s = 0; s < K4_ST; s++) {
      mbar_expect(bars + 64 + s * 8, K4_BST);
      tma3d(sb + s * K4_BST, &tmG, bars + 64 + s * 8, 0, s * 32, j * 7);
      tma3d(sb + s * K4_BST + 14336, &tmU, bars + 64 + s * 8, 0, s * 32, j * 7);
    }
    prefetch_tm(&tmA);
  }
  pdl_wait();
  if (tid == 0) {
    TL(kid, 1);
#pragma unroll
    for (int s = 0; s < 7; s++) { mbar_expect(bars + s * 8, 16384); tma2d(sm + s * 16384, &tmA, bars + s * 8, s * 64, tb * 128); }
  }
  if (tid >= 128) {
    float2 st = row_stats(tb * 128 + tid - 128);
    sts64(aux + (tid - 128) * 8, __float_as_uint(st.x), __float_as_uint(st.y));
  }
  if (tid < 224) {
    sts32(aux + 1024 + tid * 4, __float_as_uint(__ldcg(g_cs + NQ_ + j * 224 + tid)));
    sts32(aux + 1920 + tid * 4, __float_as_uint(__ldcg(g_cs + NQ_ + F_ + j * 224 + tid)));
  }
  __syncthreads();
  {
    const int wg = warp >> 2;
    float ag[112], au[112];
    int s = 0, ph = 0;
#pragma unroll 1
    for (int kc = 0; kc < 14; kc++) {
      if ((kc & 1) == 0) mbar_wait(bars + (kc >> 1) * 8, 0);
      mbar_wait(bars + 64 + s * 8, ph);
      const uint32_t a0 = sm + (kc >> 1) * 16384 + wg * 8192 + (kc & 1) * 64, b0 = sb + s * K4_BST;
      wg_fence();
#pragma unroll
      for (int k = 0; k < 2; k++) {
        const uint64_t da = mkdesc(a0 + k * 32, 16, 1024, 1);
        wgmma_ss_n224<1>(ag, da, mkdesc(b0 + k * 1024, 2048, 512, 2), kc + k);
        wgmma_ss_n224<1>(au, da, mkdesc(b0 + 14336 + k * 1024, 2048, 512, 2), kc + k);
      }
      wg_commit();
      if (kc > 0 && kc + K4_ST - 1 < 14) {
        wg_wait<1>();
        const int sp = s == 0 ? K4_ST - 1 : s - 1;
        if ((tid & 127) == 0) mbar_arrive(bars + 96 + sp * 8);
        if (tid == 0) {
          mbar_wait(bars + 96 + sp * 8, s == 0 ? ph ^ 1 : ph);
          mbar_expect(bars + 64 + sp * 8, K4_BST);
          tma3d(sb + sp * K4_BST, &tmG, bars + 64 + sp * 8, 0, (kc + K4_ST - 1) * 32, j * 7);
          tma3d(sb + sp * K4_BST + 14336, &tmU, bars + 64 + sp * 8, 0, (kc + K4_ST - 1) * 32, j * 7);
        }
        __syncwarp();
      }
      if (++s == K4_ST) { s = 0; ph ^= 1; }
    }
    wg_wait<0>();
    reg_fence(ag); reg_fence(au);
    if (tid == 0) TL(kid, 2);
    const int g = lane >> 2, t = lane & 3;
    const int r0 = wg * 64 + (warp & 3) * 16 + g;
    const float2 st0 = lds64f(aux + r0 * 8), st1 = lds64f(aux + (r0 + 8) * 8);
    const float L2E = 1.4426950408889634f;
    const float g0 = -st0.y * L2E, g1 = -st1.y * L2E;
    const int srow = (warp & 3) * 16 + (lane & 7) + ((lane >> 3) & 1) * 8;
    const uint32_t sbase = sm + wg * 8192 + srow * 64;
    const uint32_t ssw = (srow >> 1) & 3, shalf = lane >> 4;
#pragma unroll
    for (int c2 = 0; c2 < 14; c2++) {
      uint32_t r[4];
#pragma unroll
      for (int hh = 0; hh < 2; hh++) {
        const int c = c2 * 2 + hh;
        const float2 cg = lds64f(aux + 1024 + (c * 8 + 2 * t) * 4), cu = lds64f(aux + 1920 + (c * 8 + 2 * t) * 4);
        const float e0 = ex2((ag[4 * c] - st0.x * cg.x) * g0), e1 = ex2((ag[4 * c + 1] - st0.x * cg.y) * g0);
        const float e2 = ex2((ag[4 * c + 2] - st1.x * cg.x) * g1), e3 = ex2((ag[4 * c + 3] - st1.x * cg.y) * g1);
        const float h0 = (au[4 * c] - st0.x * cu.x) * st0.y * rcp(1.0f + e0), h1 = (au[4 * c + 1] - st0.x * cu.y) * st0.y * rcp(1.0f + e1);
        const float h2 = (au[4 * c + 2] - st1.x * cu.x) * st1.y * rcp(1.0f + e2), h3 = (au[4 * c + 3] - st1.x * cu.y) * st1.y * rcp(1.0f + e3);
        r[hh * 2] = pack_bf16(h0, h1); r[hh * 2 + 1] = pack_bf16(h2, h3);
      }
      stsm4(sbase + (c2 >> 1) * 16384 + (((((c2 & 1) << 1) | shalf) ^ ssw) << 4), r[0], r[1], r[2], r[3]);
    }
    fence_async();
    named_bar(2 + wg, 128);
    if ((tid & 127) < 7) {
      const int kb = tid & 127;
      bulk_st(g_h + ((size_t)(tb * 56 + j * 7 + kb) * 128 + wg * 64) * 32, sm + kb * 16384 + wg * 8192, 4096);
      bulk_commit(); bulk_wait0();
    }
    if (tid == 0) TL(kid, 3);
  }
}

typedef CUresult (*EncFn)(CUtensorMap*, CUtensorMapDataType, cuuint32_t, void*, const cuuint64_t*, const cuuint64_t*, const cuuint32_t*,
                          const cuuint32_t*, CUtensorMapInterleave, CUtensorMapSwizzle, CUtensorMapL2promotion, CUtensorMapFloatOOBfill);
static EncFn enc_fn() {
  static EncFn fn = nullptr;
  if (!fn) { cudaDriverEntryPointQueryResult q; cudaGetDriverEntryPoint("cuTensorMapEncodeTiled", (void**)&fn, cudaEnableDefault, &q); }
  return fn;
}
static CUtensorMap map2d(const void* p, int cols, int rows, int bc, int br) {
  CUtensorMap m; cuuint64_t gd[2] = {(cuuint64_t)cols, (cuuint64_t)rows}, gs[1] = {(cuuint64_t)cols * 2};
  cuuint32_t bd[2] = {(cuuint32_t)bc, (cuuint32_t)br}, es[2] = {1, 1};
  enc_fn()(&m, CU_TENSOR_MAP_DATA_TYPE_BFLOAT16, 2, (void*)p, gd, gs, bd, es, CU_TENSOR_MAP_INTERLEAVE_NONE, CU_TENSOR_MAP_SWIZZLE_128B,
           CU_TENSOR_MAP_L2_PROMOTION_L2_128B, CU_TENSOR_MAP_FLOAT_OOB_FILL_NONE);
  return m;
}
static CUtensorMap map3d_gu(const void* p) {
  CUtensorMap m; cuuint64_t gd[3] = {32, (cuuint64_t)D_, 56}, gs[2] = {(cuuint64_t)F_ * 2, 64};
  cuuint32_t bd[3] = {32, 32, 7}, es[3] = {1, 1, 1};
  enc_fn()(&m, CU_TENSOR_MAP_DATA_TYPE_BFLOAT16, 3, (void*)p, gd, gs, bd, es, CU_TENSOR_MAP_INTERLEAVE_NONE, CU_TENSOR_MAP_SWIZZLE_64B,
           CU_TENSOR_MAP_L2_PROMOTION_L2_128B, CU_TENSOR_MAP_FLOAT_OOB_FILL_NONE);
  return m;
}
template <class... KA, class... A>
static void launch(void (*k)(KA...), int grid, int block, int smem, bool pdl, A... a) {
  cudaLaunchConfig_t cfg = {};
  cfg.gridDim = dim3(grid); cfg.blockDim = dim3(block); cfg.dynamicSmemBytes = smem; cfg.stream = cudaStreamPerThread;
  cudaLaunchAttribute at[1];
  at[0].id = cudaLaunchAttributeProgrammaticStreamSerialization; at[0].val.programmaticStreamSerializationAllowed = 1;
  cfg.attrs = at; cfg.numAttrs = pdl ? 1 : 0;
  cudaLaunchKernelEx(&cfg, k, KA(a)...);
}

extern "C" void kernel_launch(void* const* d_in, const int* in_sizes, int n_in, void* d_out, int out_size) {
  const bf16* x0 = (const bf16*)d_in[0];
  const bf16* wqkv = (const bf16*)d_in[1];
  const bf16* wo = (const bf16*)d_in[2];
  const bf16* wg = (const bf16*)d_in[4];
  const bf16* wu = (const bf16*)d_in[5];
  const bf16* wd = (const bf16*)d_in[6];
  bf16* out = (bf16*)d_out;
  bf16 *px, *po;
  cudaGetSymbolAddress((void**)&px, g_x);
  cudaGetSymbolAddress((void**)&po, g_o);
  bf16* x1 = px; bf16* x2 = px + S_ * D_; bf16* x3 = px + 2 * S_ * D_;
  cudaFuncSetAttribute(k1_qkv, cudaFuncAttributeMaxDynamicSharedMemorySize, K1_SMEM);
  cudaFuncSetAttribute(k2_attn, cudaFuncAttributeMaxDynamicSharedMemorySize, K2_SMEM);
  cudaFuncSetAttribute(k3_proj<7, false>, cudaFuncAttributeMaxDynamicSharedMemorySize, K3_SMEM);
  cudaFuncSetAttribute(k3_proj<28, true>, cudaFuncAttributeMaxDynamicSharedMemorySize, K3_SMEM);
  cudaFuncSetAttribute(k4_glu, cudaFuncAttributeMaxDynamicSharedMemorySize, K4_SMEM);
  CUtensorMap mx0 = map2d(x0, D_, S_, 64, 128), mx1 = map2d(x1, D_, S_, 64, 128), mx2 = map2d(x2, D_, S_, 64, 128), mx3 = map2d(x3, D_, S_, 64, 128);
  CUtensorMap mo = map2d(po, D_, S_, 64, 128);
  CUtensorMap mwqkv = map2d(wqkv, NQ_, D_, 64, 64), mwo = map2d(wo, D_, D_, 64, 64), mwd = map2d(wd, D_, F_, 64, 64);
  CUtensorMap mwg = map3d_gu(wg), mwu = map3d_gu(wu);

  launch(k0_prep, 141, 256, 0, false, x0, wqkv, wg, wu, wo, wd);
  launch(k1_qkv, 128, 288, K1_SMEM, true, mx0, mwqkv, 1, 1);
  launch(k2_attn, 128, 512, K2_SMEM, true, 2);
  launch(k3_proj<7, false>, 128, 288, K3_SMEM, true, mo, mwo, x0, x1, 3);
  launch(k4_glu, 128, 256, K4_SMEM, true, mx1, mwg, mwu, 4);
  launch(k3_proj<28, true>, 128, 288, K3_SMEM, true, mo, mwd, (const bf16*)x1, x2, 5);
  launch(k1_qkv, 128, 288, K1_SMEM, true, mx2, mwqkv, 0, 6);
  launch(k2_attn, 128, 512, K2_SMEM, true, 7);
  launch(k3_proj<7, false>, 128, 288, K3_SMEM, true, mo, mwo, (const bf16*)x2, x3, 8);
  launch(k4_glu, 128, 256, K4_SMEM, true, mx3, mwg, mwu, 9);
  launch(k3_proj<28, true>, 128, 288, K3_SMEM, true, mo, mwd, (const bf16*)x3, out, 10);
}
```

```cpp
#include <cuda_runtime.h>
#include <cuda_bf16.h>
#include <cuda.h>
#include <stdint.h>

typedef __nv_bfloat16 bf16;
constexpr int S_ = 2048, D_ = 448, F_ = 1792, NQ_ = 1344;

constexpr int BLK = 7168;
__device__ __align__(1024) bf16 g_qkv[32 * 16 * 4096];
__device__ __align__(1024) bf16 g_ot[16 * 8 * BLK];
__device__ __align__(1024) bf16 g_xt[2][16 * 8 * BLK];
__device__ __align__(1024) bf16 g_h[16 * 32 * BLK];
__device__ __align__(1024) bf16 g_wo[8 * 4 * 6272];
__device__ __align__(1024) bf16 g_wd[8 * 16 * 6272];
__device__ __align__(1024) bf16 g_wgu[8 * 28 * BLK];
__device__ __align__(1024) bf16 g_wkv[56 * BLK];
__device__ __align__(1024) bf16 g_wq[56 * 3584];
__device__ __align__(16) float2 g_stats[2][S_ * 8];
__device__ __align__(16) float g_cs[2 * F_];
__device__ __align__(16) float g_csq[NQ_];
__device__ unsigned g_role[512];
__device__ unsigned g_seq[6 * 64];
__device__ unsigned g_kvflag[8 * 32];
__device__ unsigned g_flags[128 * 32];

__device__ __forceinline__ uint32_t s2u(const void* p) { return (uint32_t)__cvta_generic_to_shared(p); }
__device__ __forceinline__ void mbar_init(uint32_t b, int c) { asm volatile("mbarrier.init.shared::cta.b64 [%0], %1;" ::"r"(b), "r"(c) : "memory"); }
__device__ __forceinline__ void mbar_expect(uint32_t b, uint32_t bytes) { asm volatile("mbarrier.arrive.expect_tx.shared::cta.b64 _, [%0], %1;" ::"r"(b), "r"(bytes) : "memory"); }
__device__ __forceinline__ void mbar_arrive(uint32_t b) { asm volatile("mbarrier.arrive.shared::cta.b64 _, [%0];" ::"r"(b) : "memory"); }
__device__ __forceinline__ void mbar_wait(uint32_t b, uint32_t ph) {
  asm volatile("{.reg .pred p; .reg .u32 n; mov.u32 n, 0;\n"
               "W%=: mbarrier.try_wait.parity.shared::cta.b64 p, [%0], %1;\n"
               "@p bra D%=;\n"
               "add.u32 n, n, 1; setp.lt.u32 p, n, 2097152;\n"
               "@p bra W%=;\n"
               "trap;\n"
               "D%=: }" ::"r"(b), "r"(ph) : "memory");
}
__device__ __forceinline__ bool elect_one() { uint32_t p; asm volatile("{.reg .pred p; elect.sync _|p, 0xffffffff; selp.u32 %0,1,0,p;}" : "=r"(p)); return p; }
__device__ __forceinline__ void tma2d(uint32_t dst, const CUtensorMap* tm, uint32_t bar, int c0, int c1) {
  asm volatile("cp.async.bulk.tensor.2d.shared::cluster.global.mbarrier::complete_tx::bytes [%0], [%1, {%3,%4}], [%2];" ::"r"(dst), "l"(tm), "r"(bar), "r"(c0), "r"(c1) : "memory");
}
__device__ __forceinline__ void tma3d(uint32_t dst, const CUtensorMap* tm, uint32_t bar, int c0, int c1, int c2) {
  asm volatile("cp.async.bulk.tensor.3d.shared::cluster.global.mbarrier::complete_tx::bytes [%0], [%1, {%3,%4,%5}], [%2];" ::"r"(dst), "l"(tm), "r"(bar), "r"(c0), "r"(c1), "r"(c2) : "memory");
}
__device__ __forceinline__ void tma4d(uint32_t dst, const CUtensorMap* tm, uint32_t bar, int c0, int c1, int c2, int c3) {
  asm volatile("cp.async.bulk.tensor.4d.shared::cluster.global.mbarrier::complete_tx::bytes [%0], [%1, {%3,%4,%5,%6}], [%2];" ::"r"(dst), "l"(tm), "r"(bar), "r"(c0), "r"(c1), "r"(c2), "r"(c3) : "memory");
}
__device__ __forceinline__ void bulk_ld(uint32_t dst, const void* src, uint32_t bytes, uint32_t bar) {
  asm volatile("cp.async.bulk.shared::cluster.global.mbarrier::complete_tx::bytes [%0], [%1], %2, [%3];" ::"r"(dst), "l"(src), "r"(bytes), "r"(bar) : "memory");
}
__device__ __forceinline__ void bulk_st(void* dst, uint32_t src, uint32_t bytes) {
  asm volatile("cp.async.bulk.global.shared::cta.bulk_group [%0], [%1], %2;" ::"l"(dst), "r"(src), "r"(bytes) : "memory");
}
__device__ __forceinline__ void bulk_commit() { asm volatile("cp.async.bulk.commit_group;" ::: "memory"); }
__device__ __forceinline__ void bulk_wait0() { asm volatile("cp.async.bulk.wait_group 0;" ::: "memory"); }
__device__ __forceinline__ void prefetch_tm(const CUtensorMap* tm) { asm volatile("prefetch.tensormap [%0];" ::"l"(tm) : "memory"); }
__device__ __forceinline__ void fence_async() { asm volatile("fence.proxy.async.shared::cta;" ::: "memory"); }
__device__ __forceinline__ void fence_mbar_init() { asm volatile("fence.mbarrier_init.release.cluster;" ::: "memory"); }
__device__ __forceinline__ void pdl_launch() { asm volatile("griddepcontrol.launch_dependents;" ::: "memory"); }
__device__ __forceinline__ void pdl_wait() { asm volatile("griddepcontrol.wait;" ::: "memory"); }
__device__ __forceinline__ void named_bar(int id, int n) { asm volatile("bar.sync %0, %1;" ::"r"(id), "r"(n) : "memory"); }
__device__ __forceinline__ void wg_fence() { asm volatile("wgmma.fence.sync.aligned;" ::: "memory"); }
__device__ __forceinline__ void wg_commit() { asm volatile("wgmma.commit_group.sync.aligned;" ::: "memory"); }
template <int N> __device__ __forceinline__ void wg_wait() { asm volatile("wgmma.wait_group.sync.aligned %0;" ::"n"(N) : "memory"); }
template <int N> __device__ __forceinline__ void reg_fence(float (&d)[N]) {
#pragma unroll
  for (int i = 0; i < N; i++) asm volatile("" : "+f"(d[i])::"memory");
}
template <int N> __device__ __forceinline__ void reg_fence(uint32_t (&d)[N]) {
#pragma unroll
  for (int i = 0; i < N; i++) asm volatile("" : "+r"(d[i])::"memory");
}
__device__ __forceinline__ uint32_t pack_bf16(float lo, float hi) { uint32_t r; asm("cvt.rn.bf16x2.f32 %0, %1, %2;" : "=r"(r) : "f"(hi), "f"(lo)); return r; }
__device__ __forceinline__ float bf_lo(uint32_t v) { return __uint_as_float(v << 16); }
__device__ __forceinline__ float bf_hi(uint32_t v) { return __uint_as_float(v & 0xFFFF0000u); }
__device__ __forceinline__ float ex2(float x) { float r; asm("ex2.approx.ftz.f32 %0, %1;" : "=f"(r) : "f"(x)); return r; }
__device__ __forceinline__ void sts32(uint32_t a, uint32_t v) { asm volatile("st.shared.b32 [%0], %1;" ::"r"(a), "r"(v) : "memory"); }
__device__ __forceinline__ void sts64(uint32_t a, uint32_t v0, uint32_t v1) { asm volatile("st.shared.v2.b32 [%0], {%1,%2};" ::"r"(a), "r"(v0), "r"(v1) : "memory"); }
__device__ __forceinline__ void stsm4(uint32_t a, uint32_t r0, uint32_t r1, uint32_t r2, uint32_t r3) {
  asm volatile("stmatrix.sync.aligned.m8n8.x4.shared.b16 [%0], {%1,%2,%3,%4};" ::"r"(a), "r"(r0), "r"(r1), "r"(r2), "r"(r3) : "memory");
}
__device__ __forceinline__ uint4 lds128(uint32_t a) { uint4 v; asm volatile("ld.shared.v4.b32 {%0,%1,%2,%3}, [%4];" : "=r"(v.x), "=r"(v.y), "=r"(v.z), "=r"(v.w) : "r"(a) : "memory"); return v; }
__device__ __forceinline__ void stsm4t(uint32_t a, uint32_t r0, uint32_t r1, uint32_t r2, uint32_t r3) {
  asm volatile("stmatrix.sync.aligned.m8n8.x4.trans.shared.b16 [%0], {%1,%2,%3,%4};" ::"r"(a), "r"(r0), "r"(r1), "r"(r2), "r"(r3) : "memory");
}
__device__ __forceinline__ uint4 ldsm4t(uint32_t a) {
  uint4 v; asm volatile("ldmatrix.sync.aligned.m8n8.x4.trans.shared.b16 {%0,%1,%2,%3}, [%4];" : "=r"(v.x), "=r"(v.y), "=r"(v.z), "=r"(v.w) : "r"(a) : "memory"); return v;
}
__device__ __forceinline__ uint32_t lds32(uint32_t a) { uint32_t v; asm volatile("ld.shared.b32 %0, [%1];" : "=r"(v) : "r"(a) : "memory"); return v; }
__device__ __forceinline__ float lds32f(uint32_t a) { float v; asm volatile("ld.shared.f32 %0, [%1];" : "=f"(v) : "r"(a) : "memory"); return v; }
__device__ __forceinline__ float2 lds64f(uint32_t a) { float2 v; asm volatile("ld.shared.v2.f32 {%0,%1}, [%2];" : "=f"(v.x), "=f"(v.y) : "r"(a) : "memory"); return v; }

template<int TB> __device__ __forceinline__ void wgmma_ss_n56(float (&d)[28], uint64_t da, uint64_t db, int sd) {
  asm volatile("{.reg .pred p; setp.ne.b32 p, %30, 0;\n"
    "wgmma.mma_async.sync.aligned.m64n56k16.f32.bf16.bf16 {%0, %1, %2, %3, %4, %5, %6, %7, %8, %9, %10, %11, %12, %13, %14, %15, %16, %17, %18, %19, %20, %21, %22, %23, %24, %25, %26, %27}, %28, %29, p, 1, 1, 0, %31;}"
    : "+f"(d[0]), "+f"(d[1]), "+f"(d[2]), "+f"(d[3]), "+f"(d[4]), "+f"(d[5]), "+f"(d[6]), "+f"(d[7]), "+f"(d[8]), "+f"(d[9]), "+f"(d[10]), "+f"(d[11]), "+f"(d[12]), "+f"(d[13]), "+f"(d[14]), "+f"(d[15]), "+f"(d[16]), "+f"(d[17]), "+f"(d[18]), "+f"(d[19]), "+f"(d[20]), "+f"(d[21]), "+f"(d[22]), "+f"(d[23]), "+f"(d[24]), "+f"(d[25]), "+f"(d[26]), "+f"(d[27])
    : "l"(da), "l"(db), "r"(sd), "n"(TB));
}
template<int TB> __device__ __forceinline__ void wgmma_ss_n112(float (&d)[56], uint64_t da, uint64_t db, int sd) {
  asm volatile("{.reg .pred p; setp.ne.b32 p, %58, 0;\n"
    "wgmma.mma_async.sync.aligned.m64n112k16.f32.bf16.bf16 {%0, %1, %2, %3, %4, %5, %6, %7, %8, %9, %10, %11, %12, %13, %14, %15, %16, %17, %18, %19, %20, %21, %22, %23, %24, %25, %26, %27, %28, %29, %30, %31, %32, %33, %34, %35, %36, %37, %38, %39, %40, %41, %42, %43, %44, %45, %46, %47, %48, %49, %50, %51, %52, %53, %54, %55}, %56, %57, p, 1, 1, 0, %59;}"
    : "+f"(d[0]), "+f"(d[1]), "+f"(d[2]), "+f"(d[3]), "+f"(d[4]), "+f"(d[5]), "+f"(d[6]), "+f"(d[7]), "+f"(d[8]), "+f"(d[9]), "+f"(d[10]), "+f"(d[11]), "+f"(d[12]), "+f"(d[13]), "+f"(d[14]), "+f"(d[15]), "+f"(d[16]), "+f"(d[17]), "+f"(d[18]), "+f"(d[19]), "+f"(d[20]), "+f"(d[21]), "+f"(d[22]), "+f"(d[23]), "+f"(d[24]), "+f"(d[25]), "+f"(d[26]), "+f"(d[27]), "+f"(d[28]), "+f"(d[29]), "+f"(d[30]), "+f"(d[31]), "+f"(d[32]), "+f"(d[33]), "+f"(d[34]), "+f"(d[35]), "+f"(d[36]), "+f"(d[37]), "+f"(d[38]), "+f"(d[39]), "+f"(d[40]), "+f"(d[41]), "+f"(d[42]), "+f"(d[43]), "+f"(d[44]), "+f"(d[45]), "+f"(d[46]), "+f"(d[47]), "+f"(d[48]), "+f"(d[49]), "+f"(d[50]), "+f"(d[51]), "+f"(d[52]), "+f"(d[53]), "+f"(d[54]), "+f"(d[55])
    : "l"(da), "l"(db), "r"(sd), "n"(TB));
}
template<int TB> __device__ __forceinline__ void wgmma_ss_n120(float (&d)[60], uint64_t da, uint64_t db, int sd) {
  asm volatile("{.reg .pred p; setp.ne.b32 p, %62, 0;\n"
    "wgmma.mma_async.sync.aligned.m64n120k16.f32.bf16.bf16 {%0, %1, %2, %3, %4, %5, %6, %7, %8, %9, %10, %11, %12, %13, %14, %15, %16, %17, %18, %19, %20, %21, %22, %23, %24, %25, %26, %27, %28, %29, %30, %31, %32, %33, %34, %35, %36, %37, %38, %39, %40, %41, %42, %43, %44, %45, %46, %47, %48, %49, %50, %51, %52, %53, %54, %55, %56, %57, %58, %59}, %60, %61, p, 1, 1, 0, %63;}"
    : "+f"(d[0]), "+f"(d[1]), "+f"(d[2]), "+f"(d[3]), "+f"(d[4]), "+f"(d[5]), "+f"(d[6]), "+f"(d[7]), "+f"(d[8]), "+f"(d[9]), "+f"(d[10]), "+f"(d[11]), "+f"(d[12]), "+f"(d[13]), "+f"(d[14]), "+f"(d[15]), "+f"(d[16]), "+f"(d[17]), "+f"(d[18]), "+f"(d[19]), "+f"(d[20]), "+f"(d[21]), "+f"(d[22]), "+f"(d[23]), "+f"(d[24]), "+f"(d[25]), "+f"(d[26]), "+f"(d[27]), "+f"(d[28]), "+f"(d[29]), "+f"(d[30]), "+f"(d[31]), "+f"(d[32]), "+f"(d[33]), "+f"(d[34]), "+f"(d[35]), "+f"(d[36]), "+f"(d[37]), "+f"(d[38]), "+f"(d[39]), "+f"(d[40]), "+f"(d[41]), "+f"(d[42]), "+f"(d[43]), "+f"(d[44]), "+f"(d[45]), "+f"(d[46]), "+f"(d[47]), "+f"(d[48]), "+f"(d[49]), "+f"(d[50]), "+f"(d[51]), "+f"(d[52]), "+f"(d[53]), "+f"(d[54]), "+f"(d[55]), "+f"(d[56]), "+f"(d[57]), "+f"(d[58]), "+f"(d[59])
    : "l"(da), "l"(db), "r"(sd), "n"(TB));
}
template<int TB> __device__ __forceinline__ void wgmma_rs_n56(float (&d)[28], uint32_t a0, uint32_t a1, uint32_t a2, uint32_t a3, uint64_t db, int sd) {
  asm volatile("{.reg .pred p; setp.ne.b32 p, %33, 0;\n"
    "wgmma.mma_async.sync.aligned.m64n56k16.f32.bf16.bf16 {%0, %1, %2, %3, %4, %5, %6, %7, %8, %9, %10, %11, %12, %13, %14, %15, %16, %17, %18, %19, %20, %21, %22, %23, %24, %25, %26, %27}, {%28, %29, %30, %31}, %32, p, 1, 1, %34;}"
    : "+f"(d[0]), "+f"(d[1]), "+f"(d[2]), "+f"(d[3]), "+f"(d[4]), "+f"(d[5]), "+f"(d[6]), "+f"(d[7]), "+f"(d[8]), "+f"(d[9]), "+f"(d[10]), "+f"(d[11]), "+f"(d[12]), "+f"(d[13]), "+f"(d[14]), "+f"(d[15]), "+f"(d[16]), "+f"(d[17]), "+f"(d[18]), "+f"(d[19]), "+f"(d[20]), "+f"(d[21]), "+f"(d[22]), "+f"(d[23]), "+f"(d[24]), "+f"(d[25]), "+f"(d[26]), "+f"(d[27])
    : "r"(a0), "r"(a1), "r"(a2), "r"(a3), "l"(db), "r"(sd), "n"(TB));
}
template<int TB> __device__ __forceinline__ void wgmma_zh_n32(uint32_t (&d)[8], uint32_t a0, uint32_t a1, uint32_t a2, uint32_t a3, uint64_t db) {
  asm volatile("{.reg .pred p; setp.ne.b32 p, 0, 0;\n"
    "wgmma.mma_async.sync.aligned.m64n32k16.f16.f16.f16 {%0, %1, %2, %3, %4, %5, %6, %7}, {%8, %9, %10, %11}, %12, p, 1, 1, %13;}"
    : "=r"(d[0]), "=r"(d[1]), "=r"(d[2]), "=r"(d[3]), "=r"(d[4]), "=r"(d[5]), "=r"(d[6]), "=r"(d[7])
    : "r"(a0), "r"(a1), "r"(a2), "r"(a3), "l"(db), "n"(TB));
}
template<int TB> __device__ __forceinline__ void wgmma_zh_n128(uint32_t (&d)[32], uint32_t a0, uint32_t a1, uint32_t a2, uint32_t a3, uint64_t db) {
  asm volatile("{.reg .pred p; setp.ne.b32 p, 0, 0;\n"
    "wgmma.mma_async.sync.aligned.m64n128k16.f16.f16.f16 {%0, %1, %2, %3, %4, %5, %6, %7, %8, %9, %10, %11, %12, %13, %14, %15, %16, %17, %18, %19, %20, %21, %22, %23, %24, %25, %26, %27, %28, %29, %30, %31}, {%32, %33, %34, %35}, %36, p, 1, 1, %37;}"
    : "=r"(d[0]), "=r"(d[1]), "=r"(d[2]), "=r"(d[3]), "=r"(d[4]), "=r"(d[5]), "=r"(d[6]), "=r"(d[7]), "=r"(d[8]), "=r"(d[9]), "=r"(d[10]), "=r"(d[11]), "=r"(d[12]), "=r"(d[13]), "=r"(d[14]), "=r"(d[15]), "=r"(d[16]), "=r"(d[17]), "=r"(d[18]), "=r"(d[19]), "=r"(d[20]), "=r"(d[21]), "=r"(d[22]), "=r"(d[23]), "=r"(d[24]), "=r"(d[25]), "=r"(d[26]), "=r"(d[27]), "=r"(d[28]), "=r"(d[29]), "=r"(d[30]), "=r"(d[31])
    : "r"(a0), "r"(a1), "r"(a2), "r"(a3), "l"(db), "n"(TB));
}
template<int TB> __device__ __forceinline__ void wgmma_rh_n32(uint32_t (&d)[8], uint32_t a0, uint32_t a1, uint32_t a2, uint32_t a3, uint64_t db, int sd) {
  asm volatile("{.reg .pred p; setp.ne.b32 p, %13, 0;\n"
    "wgmma.mma_async.sync.aligned.m64n32k16.f16.f16.f16 {%0, %1, %2, %3, %4, %5, %6, %7}, {%8, %9, %10, %11}, %12, p, 1, 1, %14;}"
    : "+r"(d[0]), "+r"(d[1]), "+r"(d[2]), "+r"(d[3]), "+r"(d[4]), "+r"(d[5]), "+r"(d[6]), "+r"(d[7])
    : "r"(a0), "r"(a1), "r"(a2), "r"(a3), "l"(db), "r"(sd), "n"(TB));
}
template<int TB> __device__ __forceinline__ void wgmma_rh_n128(uint32_t (&d)[32], uint32_t a0, uint32_t a1, uint32_t a2, uint32_t a3, uint64_t db, int sd) {
  asm volatile("{.reg .pred p; setp.ne.b32 p, %37, 0;\n"
    "wgmma.mma_async.sync.aligned.m64n128k16.f16.f16.f16 {%0, %1, %2, %3, %4, %5, %6, %7, %8, %9, %10, %11, %12, %13, %14, %15, %16, %17, %18, %19, %20, %21, %22, %23, %24, %25, %26, %27, %28, %29, %30, %31}, {%32, %33, %34, %35}, %36, p, 1, 1, %38;}"
    : "+r"(d[0]), "+r"(d[1]), "+r"(d[2]), "+r"(d[3]), "+r"(d[4]), "+r"(d[5]), "+r"(d[6]), "+r"(d[7]), "+r"(d[8]), "+r"(d[9]), "+r"(d[10]), "+r"(d[11]), "+r"(d[12]), "+r"(d[13]), "+r"(d[14]), "+r"(d[15]), "+r"(d[16]), "+r"(d[17]), "+r"(d[18]), "+r"(d[19]), "+r"(d[20]), "+r"(d[21]), "+r"(d[22]), "+r"(d[23]), "+r"(d[24]), "+r"(d[25]), "+r"(d[26]), "+r"(d[27]), "+r"(d[28]), "+r"(d[29]), "+r"(d[30]), "+r"(d[31])
    : "r"(a0), "r"(a1), "r"(a2), "r"(a3), "l"(db), "r"(sd), "n"(TB));
}
template<int TB> __device__ __forceinline__ void wgmma_rf_n32(float (&d)[16], uint32_t a0, uint32_t a1, uint32_t a2, uint32_t a3, uint64_t db, int sd) {
  asm volatile("{.reg .pred p; setp.ne.b32 p, %21, 0;\n"
    "wgmma.mma_async.sync.aligned.m64n32k16.f32.f16.f16 {%0, %1, %2, %3, %4, %5, %6, %7, %8, %9, %10, %11, %12, %13, %14, %15}, {%16, %17, %18, %19}, %20, p, 1, 1, %22;}"
    : "+f"(d[0]), "+f"(d[1]), "+f"(d[2]), "+f"(d[3]), "+f"(d[4]), "+f"(d[5]), "+f"(d[6]), "+f"(d[7]), "+f"(d[8]), "+f"(d[9]), "+f"(d[10]), "+f"(d[11]), "+f"(d[12]), "+f"(d[13]), "+f"(d[14]), "+f"(d[15])
    : "r"(a0), "r"(a1), "r"(a2), "r"(a3), "l"(db), "r"(sd), "n"(TB));
}
template<int TB> __device__ __forceinline__ void wgmma_rf_n64(float (&d)[32], uint32_t a0, uint32_t a1, uint32_t a2, uint32_t a3, uint64_t db, int sd) {
  asm volatile("{.reg .pred p; setp.ne.b32 p, %37, 0;\n"
    "wgmma.mma_async.sync.aligned.m64n64k16.f32.f16.f16 {%0, %1, %2, %3, %4, %5, %6, %7, %8, %9, %10, %11, %12, %13, %14, %15, %16, %17, %18, %19, %20, %21, %22, %23, %24, %25, %26, %27, %28, %29, %30, %31}, {%32, %33, %34, %35}, %36, p, 1, 1, %38;}"
    : "+f"(d[0]), "+f"(d[1]), "+f"(d[2]), "+f"(d[3]), "+f"(d[4]), "+f"(d[5]), "+f"(d[6]), "+f"(d[7]), "+f"(d[8]), "+f"(d[9]), "+f"(d[10]), "+f"(d[11]), "+f"(d[12]), "+f"(d[13]), "+f"(d[14]), "+f"(d[15]), "+f"(d[16]), "+f"(d[17]), "+f"(d[18]), "+f"(d[19]), "+f"(d[20]), "+f"(d[21]), "+f"(d[22]), "+f"(d[23]), "+f"(d[24]), "+f"(d[25]), "+f"(d[26]), "+f"(d[27]), "+f"(d[28]), "+f"(d[29]), "+f"(d[30]), "+f"(d[31])
    : "r"(a0), "r"(a1), "r"(a2), "r"(a3), "l"(db), "r"(sd), "n"(TB));
}
template<int TB> __device__ __forceinline__ void wgmma_ta_n128(float (&d)[64], uint64_t da, uint64_t db, int sd) {
  asm volatile("{.reg .pred p; setp.ne.b32 p, %66, 0;\n"
    "wgmma.mma_async.sync.aligned.m64n128k16.f32.bf16.bf16 {%0, %1, %2, %3, %4, %5, %6, %7, %8, %9, %10, %11, %12, %13, %14, %15, %16, %17, %18, %19, %20, %21, %22, %23, %24, %25, %26, %27, %28, %29, %30, %31, %32, %33, %34, %35, %36, %37, %38, %39, %40, %41, %42, %43, %44, %45, %46, %47, %48, %49, %50, %51, %52, %53, %54, %55, %56, %57, %58, %59, %60, %61, %62, %63}, %64, %65, p, 1, 1, 1, %67;}"
    : "+f"(d[0]), "+f"(d[1]), "+f"(d[2]), "+f"(d[3]), "+f"(d[4]), "+f"(d[5]), "+f"(d[6]), "+f"(d[7]), "+f"(d[8]), "+f"(d[9]), "+f"(d[10]), "+f"(d[11]), "+f"(d[12]), "+f"(d[13]), "+f"(d[14]), "+f"(d[15]), "+f"(d[16]), "+f"(d[17]), "+f"(d[18]), "+f"(d[19]), "+f"(d[20]), "+f"(d[21]), "+f"(d[22]), "+f"(d[23]), "+f"(d[24]), "+f"(d[25]), "+f"(d[26]), "+f"(d[27]), "+f"(d[28]), "+f"(d[29]), "+f"(d[30]), "+f"(d[31]), "+f"(d[32]), "+f"(d[33]), "+f"(d[34]), "+f"(d[35]), "+f"(d[36]), "+f"(d[37]), "+f"(d[38]), "+f"(d[39]), "+f"(d[40]), "+f"(d[41]), "+f"(d[42]), "+f"(d[43]), "+f"(d[44]), "+f"(d[45]), "+f"(d[46]), "+f"(d[47]), "+f"(d[48]), "+f"(d[49]), "+f"(d[50]), "+f"(d[51]), "+f"(d[52]), "+f"(d[53]), "+f"(d[54]), "+f"(d[55]), "+f"(d[56]), "+f"(d[57]), "+f"(d[58]), "+f"(d[59]), "+f"(d[60]), "+f"(d[61]), "+f"(d[62]), "+f"(d[63])
    : "l"(da), "l"(db), "r"(sd), "n"(TB));
}
template<int TB> __device__ __forceinline__ void wgmma_zs_n128(uint32_t (&d)[32], uint64_t da, uint64_t db) {
  asm volatile("{.reg .pred p; setp.ne.b32 p, 0, 0;\n"
    "wgmma.mma_async.sync.aligned.m64n128k16.f16.f16.f16 {%0, %1, %2, %3, %4, %5, %6, %7, %8, %9, %10, %11, %12, %13, %14, %15, %16, %17, %18, %19, %20, %21, %22, %23, %24, %25, %26, %27, %28, %29, %30, %31}, %32, %33, p, 1, 1, 0, %34;}"
    : "=r"(d[0]), "=r"(d[1]), "=r"(d[2]), "=r"(d[3]), "=r"(d[4]), "=r"(d[5]), "=r"(d[6]), "=r"(d[7]), "=r"(d[8]), "=r"(d[9]), "=r"(d[10]), "=r"(d[11]), "=r"(d[12]), "=r"(d[13]), "=r"(d[14]), "=r"(d[15]), "=r"(d[16]), "=r"(d[17]), "=r"(d[18]), "=r"(d[19]), "=r"(d[20]), "=r"(d[21]), "=r"(d[22]), "=r"(d[23]), "=r"(d[24]), "=r"(d[25]), "=r"(d[26]), "=r"(d[27]), "=r"(d[28]), "=r"(d[29]), "=r"(d[30]), "=r"(d[31])
    : "l"(da), "l"(db), "n"(TB));
}
template<int TB> __device__ __forceinline__ void wgmma_sf_n64(float (&d)[32], uint64_t da, uint64_t db, int sd) {
  asm volatile("{.reg .pred p; setp.ne.b32 p, %34, 0;\n"
    "wgmma.mma_async.sync.aligned.m64n64k16.f32.f16.f16 {%0, %1, %2, %3, %4, %5, %6, %7, %8, %9, %10, %11, %12, %13, %14, %15, %16, %17, %18, %19, %20, %21, %22, %23, %24, %25, %26, %27, %28, %29, %30, %31}, %32, %33, p, 1, 1, 0, %35;}"
    : "+f"(d[0]), "+f"(d[1]), "+f"(d[2]), "+f"(d[3]), "+f"(d[4]), "+f"(d[5]), "+f"(d[6]), "+f"(d[7]), "+f"(d[8]), "+f"(d[9]), "+f"(d[10]), "+f"(d[11]), "+f"(d[12]), "+f"(d[13]), "+f"(d[14]), "+f"(d[15]), "+f"(d[16]), "+f"(d[17]), "+f"(d[18]), "+f"(d[19]), "+f"(d[20]), "+f"(d[21]), "+f"(d[22]), "+f"(d[23]), "+f"(d[24]), "+f"(d[25]), "+f"(d[26]), "+f"(d[27]), "+f"(d[28]), "+f"(d[29]), "+f"(d[30]), "+f"(d[31])
    : "l"(da), "l"(db), "r"(sd), "n"(TB));
}


#define MAP_TB(c) ((((c) >> 5) << 2) | (((c) >> 2) & 3))
#define MAP_J(c) (((((c) >> 4) & 1) << 2) | ((c) & 3))
#define PROXY_FENCE asm volatile("fence.proxy.async.global;" ::: "memory")
__device__ __forceinline__ uint64_t desc64(uint32_t lo, uint32_t hi) { uint64_t d; asm("mov.b64 %0, {%1,%2};" : "=l"(d) : "r"(lo), "r"(hi)); return d; }
__device__ __forceinline__ uint32_t dlo(uint32_t addr, uint32_t lbo) { return ((addr & 0x3FFFF) >> 4) | ((lbo >> 4) << 16); }
__host__ __device__ constexpr uint32_t dhi(uint32_t sbo, uint32_t swz) { return (sbo >> 4) | (swz << 30); }
__device__ __forceinline__ void named_arrive(int id, int n) { asm volatile("bar.arrive %0, %1;" ::"r"(id), "r"(n) : "memory"); }
__device__ __forceinline__ void flag_signal(unsigned* f, unsigned inc = 1u) {
  asm volatile("fence.acq_rel.gpu;\n red.relaxed.gpu.global.add.u32 [%0], %1;" ::"l"(f), "r"(inc) : "memory");
}
__device__ __forceinline__ unsigned flag_wait(const unsigned* f, unsigned target) {
  unsigned v;
  asm volatile("{.reg .pred p; .reg .u32 n, c; mov.u32 n, 0;\n"
               "W%=: ld.acquire.gpu.global.u32 %0, [%1];\n"
               "and.b32 c, %0, 65535; setp.ge.u32 p, c, %2;\n"
               "@p bra D%=;\n"
               "add.u32 n, n, 1; setp.lt.u32 p, n, 1048576;\n"
               "@p bra W%=;\n"
               "trap;\n"
               "D%=: }" : "=&r"(v) : "l"(f), "r"(target) : "memory");
  return v;
}
__device__ __forceinline__ unsigned smid() { unsigned s; asm volatile("mov.u32 %0, %%smid;" : "=r"(s)); return s; }
__device__ __forceinline__ unsigned role_load() {
  unsigned r;
  asm volatile("ld.relaxed.gpu.global.u32 %0, [%1];" : "=r"(r) : "l"(g_role + smid()) : "memory");
  return r;
}
__device__ __forceinline__ int take_role(unsigned r, int k) {
  r = __shfl_sync(~0u, r, 0);
  if (r && threadIdx.x == 0) asm volatile("red.relaxed.gpu.global.add.u32 [%0], 1;" ::"l"(g_seq + k * 64) : "memory");
  return r ? (int)r - 1 : 128;
}
__device__ __forceinline__ uint32_t pack_f16(float lo, float hi) { uint32_t r; asm("cvt.rn.satfinite.f16x2.f32 %0, %1, %2;" : "=r"(r) : "f"(hi), "f"(lo)); return r; }
__device__ __forceinline__ float tanh_fast(float x) { float r; asm("tanh.approx.f32 %0, %1;" : "=f"(r) : "f"(x)); return r; }

__device__ __forceinline__ float2 row_stats(const float2* st, int row) {
  const float2* p = st + (row >> 7) * 1024 + (row & 127);
  const float2 p0 = __ldcg(p), p1 = __ldcg(p + 128), p2 = __ldcg(p + 256), p3 = __ldcg(p + 384), p4 = __ldcg(p + 512), p5 = __ldcg(p + 640), p6 = __ldcg(p + 768), p7 = __ldcg(p + 896);
  const float4 a = make_float4(p0.x, p0.y, p1.x, p1.y), b = make_float4(p2.x, p2.y, p3.x, p3.y), c = make_float4(p4.x, p4.y, p5.x, p5.y), d = make_float4(p6.x, p6.y, p7.x, p7.y);
  float mean = (((a.x + a.z) + (b.x + b.z)) + ((c.x + c.z) + (d.x + d.z))) * (1.0f / D_);
  float m2 = ((a.y + a.w) + (b.y + b.w)) + ((c.y + c.w) + (d.y + d.w));
  const float i56 = 1.0f / 56.0f;
  float e, acc = 0.f;
  e = a.x * i56 - mean; acc += e * e;  e = a.z * i56 - mean; acc += e * e;
  e = b.x * i56 - mean; acc += e * e;  e = b.z * i56 - mean; acc += e * e;
  e = c.x * i56 - mean; acc += e * e;  e = c.z * i56 - mean; acc += e * e;
  e = d.x * i56 - mean; acc += e * e;  e = d.z * i56 - mean; acc += e * e;
  float var = (m2 + 56.0f * acc) * (1.0f / D_);
  return make_float2(mean, rsqrtf(var + 1e-5f));
}

constexpr int SLOT = 14336;
constexpr int CH_AUX = 16 * SLOT;
constexpr int CH_SMEM = CH_AUX + 2816 + 256;
struct Weights { const bf16 *wg, *wu; };
__device__ __forceinline__ void colsum_job(const Weights& W, uint32_t sm, int e, int tid) {
  const bf16* w = ((e >> 1) ? W.wu : W.wg) + (e & 1) * 896;
  const int gr = tid % 112, rg = tid / 112;
  float a[8] = {0.f, 0.f, 0.f, 0.f, 0.f, 0.f, 0.f, 0.f};
  if (rg < 2) {
#pragma unroll 1
    for (int r = 0; r < 224; r += 16) {
      uint4 v[16];
#pragma unroll
      for (int i = 0; i < 16; i++) v[i] = __ldg(reinterpret_cast<const uint4*>(w + (size_t)(rg * 224 + r + i) * F_) + gr);
#pragma unroll
      for (int i = 0; i < 16; i++) {
        a[0] += bf_lo(v[i].x); a[1] += bf_hi(v[i].x); a[2] += bf_lo(v[i].y); a[3] += bf_hi(v[i].y);
        a[4] += bf_lo(v[i].z); a[5] += bf_hi(v[i].z); a[6] += bf_lo(v[i].w); a[7] += bf_hi(v[i].w);
      }
    }
#pragma unroll
    for (int i = 0; i < 8; i++) sts32(sm + ((rg * 112 + gr) * 8 + i) * 4, __float_as_uint(a[i]));
  }
  __syncthreads();
  for (int c = tid; c < 896; c += 288) g_cs[e * 896 + c] = lds32f(sm + c * 4) + lds32f(sm + (896 + c) * 4);
}

constexpr int C2_THREADS = 512;
enum { C_PF = 0, C_XF = 5, C_GF = 9, C_PE = 18, C_ST = 24, C_GE = 25 };
constexpr uint32_t GU_RING = 0xFBEDCu;
__device__ __forceinline__ int dn_a(int b) { return (0xD4208u >> (4 * b)) & 15; }
__device__ __forceinline__ int dn_b(int b) { return (0x6CFBAu >> (4 * b)) & 15; }
constexpr int DN_EARLY = 1;
__device__ __forceinline__ int dn_buf(int w) { return w < DN_EARLY ? 0 : (w - DN_EARLY) % 5; }
__device__ __forceinline__ int dn_use(int w) { return w < DN_EARLY ? w : (w - DN_EARLY) / 5 + (dn_buf(w) == 0 ? DN_EARLY : 0); }

__device__ __forceinline__ void proj_stage(float (&acc)[64], uint32_t act, uint32_t w) {
  const uint32_t alo = dlo(w, 128), blo = dlo(act, 2048);
  wg_fence();
#pragma unroll
  for (int k = 0; k < 7; k++) wgmma_ta_n128<0>(acc, desc64(alo + k * 16, dhi(1792, 0)), desc64(blo + k * 256, dhi(128, 0)), 1);
  wg_commit();
}
template <int NC>
__device__ __forceinline__ void proj_init(float (&acc)[NC * 16], uint32_t a, int gs, int ts, int w, int lane) {
#pragma unroll
  for (int hf = 0; hf < 2; hf++)
#pragma unroll
    for (int c4 = 0; c4 < NC; c4++) {
      uint4 r = make_uint4(0u, 0u, 0u, 0u);
      if (hf == 0 || w < 3) r = ldsm4t(a + (2 * w + hf) * gs + (c4 * 32 + lane) * ts);
      float* d = acc + c4 * 16 + hf * 2;
      d[0] = bf_lo(r.x); d[1] = bf_hi(r.x); d[4] = bf_lo(r.y); d[5] = bf_hi(r.y);
      d[8] = bf_lo(r.z); d[9] = bf_hi(r.z); d[12] = bf_lo(r.w); d[13] = bf_hi(r.w);
    }
  reg_fence(acc);
}
template <int NC>
__device__ __forceinline__ void proj_finish(const float (&acc)[NC * 16], uint32_t a, int gs, int ts, int w, int lane) {
#pragma unroll
  for (int hf = 0; hf < 2; hf++)
#pragma unroll
    for (int c4 = 0; c4 < NC; c4++)
      if (hf == 0 || w < 3) {
        const float* d = acc + c4 * 16 + hf * 2;
        stsm4t(a + (2 * w + hf) * gs + (c4 * 32 + lane) * ts, pack_bf16(d[0], d[1]), pack_bf16(d[4], d[5]), pack_bf16(d[8], d[9]), pack_bf16(d[12], d[13]));
      }
}
__device__ __forceinline__ void proj_copy_out(uint32_t blk, bf16* gblk, float2* st  , int warp, int lane) {
  const int tok = warp * 16 + (lane & 15), hf = lane >> 4;
  uint4 v[4];
  uint4* gdst = reinterpret_cast<uint4*>(gblk) + hf * 512 + tok;
#pragma unroll
  for (int c = 0; c < 4; c++) v[c] = (c < 3 || !hf) ? lds128(blk + (hf * 4 + c) * 2048 + tok * 16) : make_uint4(0u, 0u, 0u, 0u);
#pragma unroll
  for (int c = 0; c < 4; c++) if (c < 3 || !hf) gdst[c * 128] = v[c];
  __syncwarp();
  float x[32], s2[2] = {0.f, 0.f}, q2[2] = {0.f, 0.f};
#pragma unroll
  for (int c = 0; c < 4; c++) {
    const uint32_t w[4] = {v[c].x, v[c].y, v[c].z, v[c].w};
#pragma unroll
    for (int k = 0; k < 4; k++) { x[c * 8 + 2 * k] = bf_lo(w[k]); x[c * 8 + 2 * k + 1] = bf_hi(w[k]); }
  }
#pragma unroll
  for (int i = 0; i < 32; i++) s2[i & 1] += x[i];
  float s = s2[0] + s2[1];
  s += __shfl_xor_sync(~0u, s, 16);
  const float mu = s * (1.0f / 56.0f), mu3 = hf ? 0.f : mu;
#pragma unroll
  for (int i = 0; i < 32; i++) { const float e = x[i] - (i < 24 ? mu : mu3); q2[i & 1] = fmaf(e, e, q2[i & 1]); }
  float q = q2[0] + q2[1];
  q += __shfl_xor_sync(~0u, q, 16);
  if (!hf) st[tok] = make_float2(s, q);
}
__device__ __forceinline__ void gather_stats(const float2* st, int tok, uint32_t aux, uint32_t st_bar) {
  const float2 r = row_stats(st, 0);
  sts64(aux + tok * 8, __float_as_uint(r.x), __float_as_uint(r.y));
  mbar_arrive(st_bar);
}

constexpr int WO_SMEM = 13 * SLOT + 64;
template <bool LAST>
__global__ void __launch_bounds__(288, 1) k_wo(const __grid_constant__ CUtensorMap tmX, const Weights W, int kid) {
  extern __shared__ __align__(1024) uint8_t smem_raw[];
  const uint32_t sm = __shfl_sync(~0u, s2u(smem_raw), 0), bars = sm + 13 * SLOT;
  const int tid = threadIdx.x, warp = __shfl_sync(~0u, tid >> 5, 0), lane = tid & 31;
  const unsigned rl = role_load();
  pdl_launch();
  if (warp < 5 && elect_one()) { mbar_init(bars + warp * 8, 1); fence_mbar_init(); }
  __syncthreads();
  const int cta = take_role(rl, LAST ? 5 : 4);
  if (cta >= 128) {
    if (!LAST) {
      for (;;) {
        __syncthreads();
        if (tid == 0) sts32(sm + 16384, atomicAdd(g_seq + 32, 1u));
        __syncthreads();
        const int e = lds32(sm + 16384);
        if (e >= 4) break;
        colsum_job(W, sm, e, tid);
      }
    }
    if (tid == 0) flag_wait(g_seq + (LAST ? 5 : 4) * 64, 128);
    return;
  }
  const int tb = MAP_TB(cta), j = MAP_J(cta);
  if (warp == 8) {
    const bool e = elect_one();
    if (e) {
      mbar_expect(bars + 32, SLOT);
      if (!LAST) tma2d(sm + 12 * SLOT, &tmX, bars + 32, j * 56, tb * 128);
      else bulk_ld(sm + 12 * SLOT, g_xt[1] + (size_t)(tb * 8 + j) * BLK, SLOT, bars + 32);
      pdl_wait();
#pragma unroll
      for (int w = 0; w < 4; w++) {
        mbar_expect(bars + w * 8, 2 * SLOT + 12544);
        bulk_ld(sm + 8 * SLOT + w * 12544, g_wo + (j * 4 + w) * 6272, 12544, bars + w * 8);
        bulk_ld(sm + 2 * w * SLOT, g_ot + (size_t)(tb * 8 + 2 * w) * BLK, 2 * SLOT, bars + w * 8);
      }
      if (LAST && cta == 0) g_seq[2 * 64] = 0;
      if (cta < 8) g_kvflag[cta * 32] = 0;
    }
    return;
  }
  if (warp < 4) {
    float acc[64];
    mbar_wait(bars + 32, 0);
    proj_init<4>(acc, sm + 12 * SLOT, LAST ? 2048 : 16, LAST ? 16 : 112, warp, lane);
#pragma unroll
    for (int w = 0; w < 4; w++) {
      mbar_wait(bars + w * 8, 0);
      proj_stage(acc, sm + 2 * w * SLOT, sm + 8 * SLOT + w * 12544);
    }
    named_bar(2, 128);
    wg_wait<0>();
    reg_fence(acc);
    proj_finish<4>(acc, sm + 12 * SLOT, 2048, 16, warp, lane);
  }
  named_bar(1, 256);
  proj_copy_out(sm + 12 * SLOT, g_xt[0] + (size_t)(tb * 8 + j) * BLK, g_stats[0] + tb * 1024 + j * 128, warp, lane);
}

template <bool LAST>
__global__ void __launch_bounds__(C2_THREADS, 1) k_chain(const __grid_constant__ CUtensorMap tmIO  , int kid) {
  extern __shared__ __align__(1024) uint8_t smem_raw[];
  const uint32_t sm = __shfl_sync(~0u, s2u(smem_raw), 0);
  const uint32_t aux = sm + CH_AUX, bars = aux + 2816;
  const int tid = threadIdx.x, warp = __shfl_sync(~0u, tid >> 5, 0), lane = tid & 31;
  const unsigned rl = role_load();
  pdl_launch();
  if (elect_one()) {
    mbar_init(bars + warp * 8, 1);
    mbar_init(bars + (warp + 16) * 8, warp + 16 == C_ST ? 128 : 1);
    fence_mbar_init();
  }
  __syncthreads();
  const int cta = take_role(rl, LAST ? 3 : 1);
  if (cta >= 128) {
    if (tid == 0) flag_wait(g_seq + (LAST ? 3 : 1) * 64, 128);
    return;
  }
  const int tb = cta >> 3, j = cta & 7;
  unsigned* flags = g_flags + tb * 256;
  if (warp == 12 && elect_one()) {
    const bf16* wgu = g_wgu + (size_t)j * 28 * BLK;
    mbar_expect(bars + C_GF * 8, SLOT);
    bulk_ld(sm + (GU_RING & 15) * SLOT, wgu, SLOT, bars + C_GF * 8);
    pdl_wait();
#pragma unroll
    for (int w = 0; w < 4; w++) {
      mbar_expect(bars + (C_XF + w) * 8, 2 * SLOT);
      bulk_ld(sm + 2 * w * SLOT, g_xt[0] + (size_t)(tb * 8 + 2 * w) * BLK, 2 * SLOT, bars + (C_XF + w) * 8);
      mbar_expect(bars + (C_GF + w + 1) * 8, SLOT);
      bulk_ld(sm + ((GU_RING >> (4 * w + 4)) & 15) * SLOT, wgu + (w + 1) * BLK, SLOT, bars + (C_GF + w + 1) * 8);
    }
  }
  __syncwarp();
  if (warp >= 12) {
    asm volatile("setmaxnreg.dec.sync.aligned.u32 48;");
    if (warp == 12) {
      const bool e = elect_one();
      const bf16* wgu = g_wgu + (size_t)j * 28 * BLK;
      int r = 0, ph = 0;
#pragma unroll 1
      for (int s = 5; s < 28; s++) {
        mbar_wait(bars + (C_GE + r) * 8, ph);
        if (e) { mbar_expect(bars + (C_GF + r) * 8, SLOT); bulk_ld(sm + ((GU_RING >> (4 * r)) & 15) * SLOT, wgu + s * BLK, SLOT, bars + (C_GF + r) * 8); }
        if (++r == 5) { r = 0; ph ^= 1; }
      }
    } else if (warp == 13) {
      const bool e = elect_one();
#pragma unroll 1
      for (int w = 0; w < 16; w++) {
        const int b = dn_buf(w), n = dn_use(w);
        if (n > 0) mbar_wait(bars + (C_PE + b) * 8, (n - 1) & 1);
        else if (b == 0) mbar_wait(bars + (C_XF + 3) * 8, 0);
        else {
          const int st = (0x1B1A1817u >> (8 * (b - 1))) & 255;
          if (b == 1) named_bar(13, 160);
          mbar_wait(bars + (C_GE + st % 5) * 8, (st / 5) & 1);
        }
        if (e) {
          mbar_expect(bars + (C_PF + b) * 8, 2 * SLOT + 12544);
          bulk_ld(sm + dn_b(b) * SLOT, g_wd + (j * 16 + w) * 6272, 12544, bars + (C_PF + b) * 8);
        }
        if ((w & 3) == 0) {
          if (w == 0) mbar_wait(bars + C_XF * 8, 0);
          mbar_wait(bars + (C_XF + (w >> 2)) * 8, 1);
        }
        if (e) bulk_ld(sm + dn_a(b) * SLOT, g_h + (size_t)(tb * 32 + 2 * w) * BLK, 2 * SLOT, bars + (C_PF + b) * 8);
      }
    } else if (warp == 14) {
      mbar_wait(bars + C_ST * 8, 0);
      if (lane == 0) {
        if (LAST) g_role[smid()] = 0;
        if (cta == 0) { g_seq[(LAST ? 5 : 4) * 64] = 0; g_seq[32] = 0; }
      }
#pragma unroll 1
      for (int u = 0; u < 4; u++) {
        flag_wait(flags + (2 + u) * 32, 8);
        PROXY_FENCE;
        if (lane == 0) mbar_arrive(bars + (C_XF + u) * 8);
      }
    } else {
#pragma unroll 1
      for (int i = 2; i < 6; i++) {
        named_bar(5 + i, 160);
        if (lane == 0) { flag_signal(flags + i * 32); }
        __syncwarp();
      }
    }
  } else if (warp >= 8) {
    const int w4 = warp - 8, tok = tid - 256;
    if (LAST && tok == 0) prefetch_tm(&tmIO);
    float acc[64];
    mbar_wait(bars + (C_XF + (j >> 1)) * 8, 0);
    proj_init<4>(acc, sm + j * SLOT, 2048, 16, w4, lane);
    named_bar(14, 256);
    gather_stats(g_stats[0] + tb * 1024 + tok, tok, aux, bars + C_ST * 8);
#pragma unroll 1
    for (int w = 0; w < 16; w++) {
      const int wu = __shfl_sync(~0u, w, 0), b = dn_buf(wu);
      if (wu == DN_EARLY + 1) named_bar(6, 256);
      mbar_wait(bars + (C_PF + b) * 8, dn_use(wu) & 1);
      proj_stage(acc, sm + dn_a(b) * SLOT, sm + dn_b(b) * SLOT);
      if (wu < DN_EARLY) {
        wg_wait<0>();
        if (tok == 0) mbar_arrive(bars + C_PE * 8);
      } else {
        wg_wait<1>();
        if (tok == 0 && wu > DN_EARLY) mbar_arrive(bars + (C_PE + dn_buf(wu - 1)) * 8);
      }
    }
    wg_wait<0>();
    reg_fence(acc);
    if (LAST) {
      proj_finish<4>(acc, sm + 7 * SLOT, 16, 112, w4, lane);
      fence_async();
      named_bar(2, 128);
      if (tok == 0) {
        asm volatile("cp.async.bulk.tensor.2d.global.shared::cta.bulk_group [%0, {%2,%3}], [%1];" ::"l"(&tmIO), "r"(sm + 7 * SLOT), "r"(j * 56), "r"(tb * 128) : "memory");
        bulk_commit();
        asm volatile("cp.async.bulk.wait_group.read 0;" ::: "memory");
      }
    } else {
      proj_finish<4>(acc, sm + 7 * SLOT, 2048, 16, w4, lane);
      named_arrive(2, 384);
    }
  } else {
    asm volatile("setmaxnreg.inc.sync.aligned.u32 168;");
    const int pair = warp >> 2, t = lane & 3, n = tid & 127;
    const int r0 = (warp & 3) * 16 + (lane >> 2);
    const bool lead = n == 0;
    const uint32_t alo = dlo(sm, 2048), blo = dlo(sm, 128);
    if (pair == 1) {
      if (!LAST) pdl_wait();
      if (n < 112) {
        const int u = n / 28;
        const float2 cg = __ldcg(reinterpret_cast<const float2*>(g_cs + j * 224) + n), cu = __ldcg(reinterpret_cast<const float2*>(g_cs + F_ + j * 224) + n);
        sts64(aux + 1024 + (n + u * 28) * 8, __float_as_uint(cg.x), __float_as_uint(cg.y));
        sts64(aux + 1024 + (n + u * 28 + 28) * 8, __float_as_uint(cu.x), __float_as_uint(cu.y));
      }
      named_arrive(14, 256);
    }
#pragma unroll 1
    for (int it = 0; it < 2; it++) {
      const int u = __shfl_sync(~0u, it * 2 + pair, 0);
      float acc[2][56];
#pragma unroll
      for (int i = 0; i < 56; i++) { acc[0][i] = 0.f; acc[1][i] = 0.f; }
      reg_fence(acc[0]); reg_fence(acc[1]);
      if (u > 0) named_bar(3 + (u & 1), 256);
      int r = (u * 7) % 5, ph = ((u * 7) / 5) & 1;
#pragma unroll
      for (int kc = 0; kc < 7; kc++) {
        mbar_wait(bars + (C_GF + r) * 8, ph);
        if (u == 0 && (kc == 0 || (kc & 1))) mbar_wait(bars + (C_XF + (kc + 1) / 2) * 8, 0);
        const uint32_t bs = blo + ((GU_RING >> (4 * r)) & 15) * (SLOT >> 4);
        wg_fence();
#pragma unroll
        for (int k = 0; k < 4; k++) {
          wgmma_ss_n112<1>(acc[0], desc64(alo + (kc * 4 + k) * 256, dhi(128, 0)), desc64(bs + k * 16, dhi(1024, 0)), 1);
          wgmma_ss_n112<1>(acc[1], desc64(alo + (kc * 4 + k) * 256 + 64, dhi(128, 0)), desc64(bs + k * 16, dhi(1024, 0)), 1);
        }
        wg_commit();
        if (kc > 0) {
          wg_wait<1>();
          if (lead) mbar_arrive(bars + (C_GE + (r == 0 ? 4 : r - 1)) * 8);
        }
        if (kc == 2 && u == 3) named_arrive(13, 160);
        if (++r == 5) { r = 0; ph ^= 1; }
      }
      if (u < 3) named_arrive(3 + ((u + 1) & 1), 256);
      wg_wait<0>();
      reg_fence(acc[0]); reg_fence(acc[1]);
      if (lead) { mbar_arrive(bars + (C_GE + (r == 0 ? 4 : r - 1)) * 8); }
      mbar_wait(bars + C_ST * 8, 0);
      float2 st[4];
#pragma unroll
      for (int i = 0; i < 4; i++) { st[i] = lds64f(aux + (r0 + (i & 1) * 8 + (i >> 1) * 64) * 8); st[i].y *= 0.5f; }
      uint32_t* dst = reinterpret_cast<uint32_t*>(g_h + (size_t)(tb * 32 + u * 8 + j) * BLK) + r0 * 4 + t;
#pragma unroll
      for (int c = 0; c < 7; c++) {
        const float2 cg = lds64f(aux + 1024 + (u * 112 + c * 8 + 2 * t) * 4), cu = lds64f(aux + 1024 + (u * 112 + 56 + c * 8 + 2 * t) * 4);
#pragma unroll
        for (int i = 0; i < 4; i++) {
          const float* a = acc[i >> 1] + 4 * c + (i & 1) * 2;
          const float t0 = tanh_fast((a[0] - st[i].x * cg.x) * st[i].y), t1 = tanh_fast((a[1] - st[i].x * cg.y) * st[i].y);
          const float v0 = (a[28] - st[i].x * cu.x) * st[i].y, v1 = (a[29] - st[i].x * cu.y) * st[i].y;
          dst[c * 512 + (i & 1) * 32 + (i >> 1) * 256] = pack_bf16(fmaf(v0, t0, v0), fmaf(v1, t1, v1));
        }
        if (c == 4 && u == 3) named_arrive(6, 256);
      }
      named_arrive(7 + u, 160);
    }
    if (!LAST) {
      named_bar(2, 384);
      proj_copy_out(sm + 7 * SLOT, g_xt[1] + (size_t)(tb * 8 + j) * BLK, g_stats[1] + tb * 1024 + j * 128, warp, lane);
    }
  }
}

constexpr int K2_ST = 6, K2_STAGE = 32768;
constexpr int K2_SMEM = CH_SMEM;
constexpr uint32_t KQ_HI = dhi(128, 0), V_HI = dhi(2048, 0);
template <bool QSM>
__device__ __forceinline__ void qk128(uint32_t (&s)[32], uint32_t qlo, const uint32_t (&q)[8], uint32_t klo, uint32_t khi) {
  wg_fence();
  if (QSM) wgmma_zs_n128<0>(s, desc64(qlo, khi), desc64(klo, khi));
  else wgmma_zh_n128<0>(s, q[0], q[1], q[2], q[3], desc64(klo, khi));
  wgmma_rh_n128<0>(s, q[4], q[5], q[6], q[7], desc64(klo ^ 256, khi), 1);
  wg_commit();
}
template <int K0, int K1>
__device__ __forceinline__ void pv128(float (&o)[16], const uint32_t (&p)[32], uint32_t vlo, uint32_t vhi) {
  wg_fence();
#pragma unroll
  for (int k = K0; k < K1; k++) wgmma_rf_n32<1>(o, p[4 * k], p[4 * k + 1], p[4 * k + 2], p[4 * k + 3], desc64(vlo + k * 16, vhi), 1);
  wg_commit();
}
template <int K0, int K1, bool FRESH>
__device__ __forceinline__ void pv128h(uint32_t (&oh)[8], const uint32_t (&p)[32], uint32_t vlo, uint32_t vhi) {
  if (FRESH && K0 == 0) wg_wait<0>();
  wg_fence();
#pragma unroll
  for (int k = K0; k < K1; k++) {
    if (FRESH && k == 0) wgmma_zh_n32<1>(oh, p[0], p[1], p[2], p[3], desc64(vlo, vhi));
    else wgmma_rh_n32<1>(oh, p[4 * k], p[4 * k + 1], p[4 * k + 2], p[4 * k + 3], desc64(vlo + k * 16, vhi), 1);
  }
  wg_commit();
}
__device__ __forceinline__ void o_fold(float (&o)[16], const uint32_t (&oh)[8], uint32_t ilo) {
  wg_fence();
  wgmma_rf_n32<1>(o, oh[0], oh[1], oh[2], oh[3], desc64(ilo, dhi(128, 0)), 1);
  wgmma_rf_n32<1>(o, oh[4], oh[5], oh[6], oh[7], desc64(ilo + 16, dhi(128, 0)), 1);
  wg_commit();
}
__device__ __forceinline__ uint32_t ex2_h2(uint32_t x) { uint32_t r; asm("ex2.approx.f16x2 %0, %1;" : "=r"(r) : "r"(x)); return r; }
__device__ __forceinline__ uint32_t ex2_fma2(uint32_t x, uint32_t mg  , uint32_t& t) {
  uint32_t r;
  asm("{.reg .b32 n, f, p, e;\n"
      "add.rn.f16x2 %1, %2, %3;\n"
      "sub.rn.f16x2 n, %1, %4;\n"
      "sub.rn.f16x2 f, %2, n;\n"
      "fma.rn.f16x2 p, f, %5, %6;\n"
      "fma.rn.f16x2 p, p, f, %7;\n"
      "fma.rn.f16x2 p, p, f, %8;\n"
      "mad.lo.u32 e, %1, 1024, %9;\n"
      "fma.rn.relu.f16x2 %0, p, e, %10;}"
      : "=r"(r), "=&r"(t) : "r"(x), "r"(mg), "r"(0x662F662Fu), "r"(0xAAF2AAF2u), "r"(0xB3BFB3BFu), "r"(0xB98CB98Cu), "r"(0xBC00BC00u),
        "r"(0u - (0x198u << 16)), "r"(0u));
  return r;
}
constexpr uint32_t POLY_MASK = 0x55495549u;
constexpr uint32_t CHAIN_MASK = 0x80808080u;
template <int I0, int I1>
__device__ __forceinline__ void softmax_h(uint32_t (&s)[32], uint32_t& lo, uint32_t& ovf, uint32_t zero) {
#pragma unroll
  for (int i = I0; i < I1; i++) {
    if ((POLY_MASK >> i) & 1) { uint32_t t; s[i] = ex2_fma2(s[i], lo, t); ovf |= t; }
    else s[i] = ex2_h2(s[i]);
    if ((CHAIN_MASK >> i) & 1) lo = (s[i] & zero) | 0x662F662Fu;
  }
#pragma unroll
  for (int i = I0; i < I1; i++) asm volatile("" : "+r"(s[i])::"memory");
}
constexpr int NSPLIT = 4;
template <int G, bool FRESH>
__device__ __forceinline__ void sm_pv(uint32_t (&oh)[8], uint32_t (&s)[32], uint32_t& lo, uint32_t& ovf, uint32_t zero, uint32_t vlo) {
  softmax_h<G * (32 / NSPLIT), (G + 1) * (32 / NSPLIT)>(s, lo, ovf, zero);
  pv128h<G * (8 / NSPLIT), (G + 1) * (8 / NSPLIT), FRESH>(oh, s, vlo, V_HI | (vlo & zero));
  if constexpr (G + 1 < NSPLIT) sm_pv<G + 1, FRESH>(oh, s, lo, ovf, zero, vlo);
}
__device__ __forceinline__ uint32_t hmax2(uint32_t a, uint32_t b) { uint32_t r; asm("max.NaN.f16x2 %0, %1, %2;" : "=r"(r) : "r"(a), "r"(b)); return r; }
__device__ __forceinline__ void rowmax64(const float (&s)[32], float& m0, float& m1) {
  m0 = fmaxf(s[0], s[1]); m1 = fmaxf(s[2], s[3]);
#pragma unroll
  for (int c = 1; c < 8; c++) { m0 = fmaxf(m0, fmaxf(s[4 * c], s[4 * c + 1])); m1 = fmaxf(m1, fmaxf(s[4 * c + 2], s[4 * c + 3])); }
  m0 = fmaxf(m0, __shfl_xor_sync(~0u, m0, 1)); m0 = fmaxf(m0, __shfl_xor_sync(~0u, m0, 2));
  m1 = fmaxf(m1, __shfl_xor_sync(~0u, m1, 1)); m1 = fmaxf(m1, __shfl_xor_sync(~0u, m1, 2));
}
__device__ __forceinline__ void kv_load(uint32_t dst, uint32_t bar, const bf16* src, uint32_t bytes) {
  mbar_expect(bar, bytes);
  bulk_ld(dst, src, bytes, bar);
}

struct PackMaps { CUtensorMap g, u, d, o, q, xa, wb; };
__device__ __forceinline__ void repack_step(const PackMaps& P, uint32_t st, uint32_t bar, int step, int c) {
  if (step & 1) mbar_wait(bar, step >> 1);
  if (elect_one()) {
    if (step == 0) {
      mbar_expect(bar, 12544 + SLOT);
      tma4d(st, &P.d, bar, 0, ((c >> 2) & 3) * 56, (c & 3) * 2, (c >> 4) * 7);
      tma3d(st + SLOT, &P.g, bar, 0, (c % 7) * 64, (c / 7) * 7);
      tma3d(st + SLOT + 7168, &P.u, bar, 0, (c % 7) * 64, (c / 7) * 7);
    } else if (step == 1) {
      bulk_st(g_wd + c * 6272, st, 12544);
      bulk_st(g_wgu + c * BLK, st + SLOT, SLOT);
      bulk_commit();
    } else if (step == 2) {
      asm volatile("cp.async.bulk.wait_group.read 0;" ::: "memory");
      mbar_expect(bar, (c < 96 ? SLOT : 12544) + (c < 56 ? SLOT : c < 112 ? 7168 : 0));
      const int c2 = c + 128, mm = (c % 56) / 7;
      if (c < 96) {
        tma3d(st, &P.g, bar, 0, (c2 % 7) * 64, (c2 / 7) * 7);
        tma3d(st + 7168, &P.u, bar, 0, (c2 % 7) * 64, (c2 / 7) * 7);
      } else tma3d(st, &P.o, bar, 0, (c & 3) * 112, ((c - 96) >> 2) * 7);
      if (c < 112) tma3d(st + SLOT, &P.q, bar, 0, (c % 7) * 64, (c < 56 ? 56 : 0) + mm * 7);
      if (c < 56) tma3d(st + SLOT + 7168, &P.q, bar, 0, (c % 7) * 64, 112 + mm * 7);
    } else {
      if (c < 96) bulk_st(g_wgu + (c + 128) * BLK, st, SLOT);
      else bulk_st(g_wo + (c - 96) * 6272, st, 12544);
      if (c < 56) bulk_st(g_wkv + c * BLK, st + SLOT, SLOT);
      else if (c < 112) bulk_st(g_wq + (c - 56) * 3584, st + SLOT, 7168);
      bulk_commit();
    }
  }
}

template <int NA>
__device__ __forceinline__ bool pair_stage(const float (&acc)[NA], int a0, uint32_t ev, uint32_t od, const float2* cs, float2 st0, float2 st1, uint32_t padv, int t,
                                           uint32_t lim) {
  uint32_t v[14];
#pragma unroll
  for (int c = 0; c < 7; c++) {
    const float* a = acc + a0 + 4 * c;
    v[2 * c] = pack_f16((a[0] - st0.x * cs[c].x) * st0.y, (a[1] - st0.x * cs[c].y) * st0.y);
    v[2 * c + 1] = pack_f16((a[2] - st1.x * cs[c].x) * st1.y, (a[3] - st1.x * cs[c].y) * st1.y);
  }
  stsm4(ev, v[0], v[1], v[2], v[3]);
  stsm4(ev + 4096, v[4], v[5], t < 2 ? v[6] : padv, t < 2 ? v[7] : padv);
  stsm4(od, t < 2 ? padv : v[6], t < 2 ? padv : v[7], v[8], v[9]);
  stsm4(od + 4096, v[10], v[11], v[12], v[13]);
  uint32_t n2 = 0u, ok;
#pragma unroll
  for (int i = 0; i < 14; i++) asm("fma.rn.f16x2 %0, %1, %1, %0;" : "+r"(n2) : "r"(v[i]));
  asm("set.le.u32.f16x2 %0, %1, %2;" : "=r"(ok) : "r"(n2), "r"(lim));
  return ok == 0xFFFFFFFFu;
}
constexpr uint32_t K_LIM = 0x57005700u, Q_LIM = 0x48004800u;

template <bool first>
__global__ void __launch_bounds__(512, 1) k2_attn(const __grid_constant__ PackMaps P, int kid) {
  extern __shared__ __align__(1024) uint8_t smem_raw[];
  const uint32_t sm = __shfl_sync(~0u, s2u(smem_raw), 0);
  const uint32_t aux = sm + CH_AUX, bars = aux + 2816;
  const int tid = threadIdx.x, warp = __shfl_sync(~0u, tid >> 5, 0), lane = tid & 31;
  unsigned rl = 0;
  if (!first) { rl = role_load(); pdl_launch(); }
  if (first && warp == 3) {
    const bool e = elect_one();
    if (e) {
      mbar_init(bars + 24, 1);
#pragma unroll
      for (int i = 0; i < 7; i++) mbar_init(bars + 160 + i * 8, 1);
      fence_mbar_init();
    }
    __syncwarp();
    named_arrive(1, 512);
    if (e) {
      const int m = MAP_J(blockIdx.x), tb = MAP_TB(blockIdx.x);
#pragma unroll
      for (int kc = 0; kc < 7; kc++) {
        const uint32_t bar = bars + 160 + kc * 8, wdst = sm + ((kc + 2) % 7) * 16384;
        mbar_expect(bar, (kc < 3 ? 32768 : kc == 3 ? 16384 : 0) + 14336);
        if (kc < 4) tma2d(sm + (7 + 2 * kc) * 16384, &P.xa, bar, kc * 128, tb * 128);
        tma2d(wdst, &P.wb, bar, D_ + m * 56, kc * 64);
        tma2d(wdst + 8192, &P.wb, bar, 2 * D_ + m * 56, kc * 64);
        if (kc < 3) tma2d(sm + (8 + 2 * kc) * 16384, &P.xa, bar, kc * 128 + 64, tb * 128);
      }
      if (tb < 7) asm volatile("cp.async.bulk.prefetch.tensor.2d.L2.global [%0, {%1,%2}];" ::"l"(&P.wb), "r"(m * 56), "r"(tb * 64) : "memory");
    }
    __syncwarp();
  } else {
    if (elect_one()) {
      if ((sm & 8191) != 1024) __trap();
      if (warp == 0) sts32(aux + 1728, 0u);
      mbar_init(bars + warp * 8, (warp >= 8 && warp < 11) ? 4 : (warp >= 4 && warp < 8) ? (first ? 4 : 2) : 1);
      if (!first || warp >= 11) mbar_init(bars + 128 + warp * 8, 1);
      fence_mbar_init();
    }
    if (tid >= 256 && tid < 256 + 224) {
      const int w = tid - 256 - 96;
      sts32(aux + 1792 + (tid - 256) * 4, (w >= 0 && w < 32 && (w & 3) == (w >> 3)) ? ((w & 4) ? 0x3C000000u : 0x3C00u) : 0u);
      fence_async();
    }
    __syncwarp();
    named_bar(1, 512);
  }
  const int cta = first ? blockIdx.x : take_role(rl, 2);
  if (cta >= 128) {
    if (tid == 0) flag_wait(g_seq + 2 * 64, 128);
    return;
  }
  const int m = MAP_J(cta), tb = MAP_TB(cta);
  const int own = tb >> 1;
  const int wg = warp >> 2, hd = wg >> 1, rh = wg & 1;
  const bf16* kv = g_qkv + m * 16 * 16384;
  const int g = lane >> 2, t = lane & 3;
  const int r0 = rh * 64 + (warp & 3) * 16 + g;
  constexpr bool QSM = !first;
  uint32_t q[8], ovf = 0u;
  const uint32_t srow = (rh * 64 + (warp & 3) * 16 + (lane & 15)) * 16 + (lane >> 4) * 2048;
  const float qs = 0.18898223650461362f * 1.4426950408889634f;
  if (first) {
    const uint32_t alo = dlo(sm + 7 * 16384 + rh * 8192, 16), blo = dlo(sm, 8192);
    uint32_t one[4];
#pragma unroll
    for (int i = 0; i < 4; i++) one[i] = 0x3F803F80u + ((kid >> 16) << i);
    reg_fence(one);
    if (hd == 0) {
      if (tid == 0) {
        g_role[smid()] = cta + 1;
        g_flags[cta * 32] = 0;
        if (cta == 0) g_seq[3 * 64] = 0;
        asm volatile("fence.acq_rel.gpu;" ::: "memory");
        pdl_launch();
      }
      __syncwarp();
      {
        float acc[60];
#pragma unroll
        for (int i = 0; i < 60; i++) acc[i] = 0.f;
        reg_fence(acc);
#pragma unroll
        for (int kc = 0; kc < 7; kc++) {
          mbar_wait(bars + 160 + kc * 8, 0);
          wg_fence();
#pragma unroll
          for (int k = 0; k < 4; k++)
            wgmma_ss_n120<1>(acc, desc64(alo + kc * 1024 + k * 2, dhi(1024, 1)), desc64(blo + ((kc + 2) % 7) * 1024 + k * 128, dhi(1024, 1)), 1);
          wg_commit();
          if (kc > 0 && kc < 5) {
            wg_wait<1>();
            if ((tid & 127) == 0) mbar_arrive(bars + 32 + (kc - 1) * 8);
          }
        }
        wg_wait<0>();
        reg_fence(acc);
        named_bar(2, 512);
        const float2 st0 = lds64f(aux + r0 * 8), st1 = lds64f(aux + (r0 + 8) * 8);
        float2 cs[14];
#pragma unroll
        for (int c = 0; c < 14; c++) cs[c] = lds64f(aux + 1024 + 224 + (c * 8 + 2 * t) * 4);
        const uint32_t padv = (t & 1) ? 0u : 0x3C00u;
        if (!pair_stage(acc, 0, sm + srow, sm + srow + 16384, cs, st0, st1, padv, t, K_LIM)) sts32(aux + 1728, 65536u);
        pair_stage(acc, 32, sm + srow + 8192, sm + srow + 24576, cs + 7, st0, st1, padv, t, K_LIM);
      }
      fence_async();
      named_arrive(3, 512);
      if (warp == 0) {
        named_bar(4, 256);
        if (elect_one()) { bulk_st(g_qkv + (m * 16 + tb) * 16384, sm, K2_STAGE); bulk_commit(); }
        __syncwarp();
      } else named_arrive(4, 256);
      if (rh == 1) {
        float acc[28];
#pragma unroll
        for (int i = 0; i < 28; i++) acc[i] = 0.f;
        reg_fence(acc);
#pragma unroll
        for (int kc = 0; kc < 7; kc++) {
          if ((kc & 1) == 0) mbar_wait(bars + 216 + (kc >> 1) * 8, 0);
          wg_fence();
#pragma unroll
          for (int k = 0; k < 4; k++) wgmma_rs_n56<1>(acc, one[0], one[1], one[2], one[3], desc64(blo + 2048 + kc * 512 + k * 128, dhi(1024, 1)), 1);
          wg_commit();
        }
        wg_wait<0>();
        reg_fence(acc);
        if (tid < 132) {
#pragma unroll
          for (int c = 0; c < 7; c++) {
            sts64(aux + 1024 + (c * 8 + 2 * t) * 4, __float_as_uint(acc[4 * c]), __float_as_uint(acc[4 * c + 1]));
            if (tb == 0) *reinterpret_cast<float2*>(g_csq + m * 168 + c * 8 + 2 * t) = make_float2(acc[4 * c], acc[4 * c + 1]);
          }
        }
        named_arrive(5, 384);
      }
    } else {
      {
        float acc[28];
#pragma unroll
        for (int i = 0; i < 28; i++) acc[i] = 0.f;
        reg_fence(acc);
        const int row = (warp - 8) * 16 + (lane & 15), hf = lane >> 4;
        float s0 = 0.f, s1 = 0.f, q0 = 0.f, q1 = 0.f;
#pragma unroll
        for (int i = 0; i < 7; i++) {
          mbar_wait(bars + 160 + i * 8, 0);
          wg_fence();
#pragma unroll
          for (int k = 0; k < 4; k++) wgmma_rs_n56<1>(acc, one[0], one[1], one[2], one[3], desc64(blo + rh * 512 + ((i + 2) % 7) * 1024 + k * 128, dhi(1024, 1)), 1);
          wg_commit();
          if (i < 4) {
#pragma unroll
            for (int c = 0; c < 7; c++) {
              const int gr = (2 * i + hf) * 7 + c;
              const uint4 v = lds128(sm + (7 + (gr >> 3)) * 16384 + row * 128 + (((gr & 7) ^ (row & 7)) << 4));
              const uint32_t w4[4] = {v.x, v.y, v.z, v.w};
#pragma unroll
              for (int k = 0; k < 4; k++) {
                const float e0 = bf_lo(w4[k]), e1 = bf_hi(w4[k]);
                s0 += e0; s1 += e1; q0 = fmaf(e0, e0, q0); q1 = fmaf(e1, e1, q1);
              }
            }
            wg_wait<0>();
            if ((tid & 127) == 0) mbar_arrive(bars + 32 + i * 8);
          }
          if (i == 3) {
            s0 += s1; q0 += q1;
            s0 += __shfl_xor_sync(~0u, s0, 16); q0 += __shfl_xor_sync(~0u, q0, 16);
            const float mean = s0 * (1.0f / D_), var = fmaxf(q0 * (1.0f / D_) - mean * mean, 0.f);
            if (hf == 0) sts64(aux + row * 8, __float_as_uint(mean), __float_as_uint(rsqrtf(var + 1e-5f)));
          }
        }
        if (warp == 15) {
          named_arrive(2, 512);
          const bool e = elect_one();
#pragma unroll 1
          for (int s = 0; s < 4; s++) {
            mbar_wait(bars + 32 + s * 8, 0);
            if (e) {
              mbar_expect(bars + 216 + s * 8, s < 3 ? 14336 : 7168);
              tma2d(sm + (2 + s) * 16384, &P.wb, bars + 216 + s * 8, m * 56, s * 128);
              if (s < 3) tma2d(sm + (2 + s) * 16384 + 8192, &P.wb, bars + 216 + s * 8, m * 56, s * 128 + 64);
            }
          }
          __syncwarp();
        }
        wg_wait<0>();
        reg_fence(acc);
        if ((tid & 127) < 4) {
#pragma unroll
          for (int c = 0; c < 7; c++) {
            sts64(aux + 1024 + 224 + (rh * 56 + c * 8 + 2 * t) * 4, __float_as_uint(acc[4 * c]), __float_as_uint(acc[4 * c + 1]));
            if (tb == 0) *reinterpret_cast<float2*>(g_csq + m * 168 + 56 + rh * 56 + c * 8 + 2 * t) = make_float2(acc[4 * c], acc[4 * c + 1]);
          }
        }
        if (warp != 15) named_arrive(2, 512);
      }
      float acc[28];
#pragma unroll
      for (int i = 0; i < 28; i++) acc[i] = 0.f;
      reg_fence(acc);
      named_bar(3, 512);
#pragma unroll
      for (int kc = 0; kc < 7; kc++) {
        if ((kc & 1) == 0) mbar_wait(bars + 216 + (kc >> 1) * 8, 0);
        wg_fence();
#pragma unroll
        for (int k = 0; k < 4; k++) wgmma_ss_n56<1>(acc, desc64(alo + kc * 1024 + k * 2, dhi(1024, 1)), desc64(blo + 2048 + kc * 512 + k * 128, dhi(1024, 1)), 1);
        wg_commit();
      }
      wg_wait<0>();
      reg_fence(acc);
      named_bar(5, 384);
      float2 st0 = lds64f(aux + r0 * 8), st1 = lds64f(aux + (r0 + 8) * 8), cs[7];
#pragma unroll
      for (int c = 0; c < 7; c++) cs[c] = lds64f(aux + 1024 + (c * 8 + 2 * t) * 4);
      st0.y *= qs; st1.y *= qs;
      if (!pair_stage(acc, 0, sm + 6 * K2_STAGE + srow, sm + 6 * K2_STAGE + srow + 8192, cs, st0, st1, 0u, t, Q_LIM)) ovf = ~0u;
    }
  } else {
    const uint32_t alo = dlo(sm + 8 * SLOT + rh * 1024, 2048), blo = dlo(sm, 128);
    if (hd == 0) {
      float acc[56];
#pragma unroll
      for (int i = 0; i < 56; i++) acc[i] = 0.f;
      reg_fence(acc);
#pragma unroll
      for (int kc = 0; kc < 7; kc++) {
        mbar_wait(bars + 160 + kc * 8, 0);
        if (kc == 0 || (kc & 1)) mbar_wait(bars + 128 + ((kc + 1) / 2) * 8, 0);
        wg_fence();
#pragma unroll
        for (int k = 0; k < 4; k++)
          wgmma_ss_n112<1>(acc, desc64(alo + (kc * 4 + k) * 256, dhi(128, 0)), desc64(blo + ((kc + 3) % 7) * (SLOT >> 4) + k * 16, dhi(1024, 0)), 1);
        wg_commit();
        if (kc > 0 && kc < 4) {
          wg_wait<1>();
          if ((tid & 127) == 0) mbar_arrive(bars + 32 + (kc - 1) * 8);
        }
      }
      named_bar(2, 512);
      const float2 st0 = lds64f(aux + r0 * 8), st1 = lds64f(aux + (r0 + 8) * 8);
      float2 cs[14];
#pragma unroll
      for (int c = 0; c < 14; c++) cs[c] = lds64f(aux + 1024 + 224 + (c * 8 + 2 * t) * 4);
      wg_wait<0>();
      reg_fence(acc);
      named_bar(6, 256);
      const uint32_t padv = (t & 1) ? 0u : 0x3C00u;
      if (!pair_stage(acc, 0, sm + srow, sm + srow + 16384, cs, st0, st1, padv, t, K_LIM)) sts32(aux + 1728, 65536u);
      pair_stage(acc, 28, sm + srow + 8192, sm + srow + 24576, cs + 7, st0, st1, padv, t, K_LIM);
      fence_async();
      named_arrive(3, 512);
      if (warp == 0) {
        named_bar(4, 256);
        if (elect_one()) { bulk_st(g_qkv + (m * 16 + tb) * 16384, sm, K2_STAGE); bulk_commit(); }
        __syncwarp();
      } else named_arrive(4, 256);
    } else {
      if (warp == 15) {
        const bool e = elect_one();
        const bf16 *wkv = g_wkv + m * 7 * BLK, *wq = g_wq + m * 7 * 3584;
        if (e) {
          kv_load(sm + 3 * SLOT, bars + 160, wkv, SLOT);
          pdl_wait();
#pragma unroll
          for (int w = 0; w < 6; w++) {
            if (w < 4) kv_load(sm + (8 + 2 * w) * SLOT, bars + 128 + w * 8, g_xt[1] + (size_t)(tb * 8 + 2 * w) * BLK, 2 * SLOT);
            kv_load(sm + ((w + 4) % 7) * SLOT, bars + 160 + (w + 1) * 8, wkv + (w + 1) * BLK, SLOT);
          }
          kv_load(sm + 7 * SLOT, bars + 216, wq, SLOT);
          g_flags[cta * 32] = 0;
          if (cta == 0) g_seq[64] = 0;
        }
#pragma unroll 1
        for (int s = 0; s < 3; s++) {
          mbar_wait(bars + 32 + s * 8, 0);
          if (e) kv_load(sm + (3 + s) * SLOT, bars + 224 + s * 8, wq + (s + 1) * BLK, s < 2 ? SLOT : 7168);
        }
        __syncwarp();
      } else if (warp >= 12) {
        if (tid < 384 + 84) { const float2 c = __ldcg(reinterpret_cast<const float2*>(g_csq + m * 168) + tid - 384); sts64(aux + 1024 + (tid - 384) * 8, __float_as_uint(c.x), __float_as_uint(c.y)); }
      } else {
        pdl_wait();
        const float2 s = row_stats(g_stats[1], tb * 128 + tid - 256);
        sts64(aux + (tid - 256) * 8, __float_as_uint(s.x), __float_as_uint(s.y));
      }
      named_arrive(2, 512);
      float acc[28];
#pragma unroll
      for (int i = 0; i < 28; i++) acc[i] = 0.f;
      reg_fence(acc);
      named_bar(7, 256);
      float2 st0 = lds64f(aux + r0 * 8), st1 = lds64f(aux + (r0 + 8) * 8), cs[7];
#pragma unroll
      for (int c = 0; c < 7; c++) cs[c] = lds64f(aux + 1024 + (c * 8 + 2 * t) * 4);
      named_bar(3, 512);
#pragma unroll
      for (int kc = 0; kc < 7; kc++) {
        if ((kc & 1) == 0) mbar_wait(bars + 216 + (kc >> 1) * 8, 0);
        wg_fence();
#pragma unroll
        for (int k = 0; k < 4; k++)
          wgmma_ss_n56<1>(acc, desc64(alo + (kc * 4 + k) * 256, dhi(128, 0)), desc64(blo + (kc < 2 ? 7 : 2 + (kc >> 1)) * (SLOT >> 4) + (kc & 1) * 448 + k * 16, dhi(1024, 0)), 1);
        wg_commit();
      }
      st0.y *= qs; st1.y *= qs;
      wg_wait<0>();
      reg_fence(acc);
      named_bar(5, 256);
      if (!pair_stage(acc, 0, sm + 6 * K2_STAGE + srow, sm + 6 * K2_STAGE + srow + 8192, cs, st0, st1, 0u, t, Q_LIM)) ovf = ~0u;
      fence_async();
    }
  }
  if (warp == 0) {
    if (elect_one()) { bulk_wait0(); flag_signal(g_kvflag + m * 32, 1u + lds32(aux + 1728)); }
    __syncwarp();
    if (flag_wait(g_kvflag + m * 32, 16) >> 16) ovf = ~0u;
    PROXY_FENCE;
    named_bar(9, 288);
    if (elect_one()) {
      kv_load(sm + K2_STAGE, bars, kv + (tb ^ 1) * 16384, K2_STAGE);
      kv_load(sm + 2 * K2_STAGE, bars + 8, kv + (own == 0 ? 1 : 0) * 32768, 2 * K2_STAGE);
      mbar_arrive(bars + 24);
    }
    __syncwarp();
  } else {
    if (hd) named_arrive(9, 288);
    named_bar(8, 480);
  }
  {
    const uint32_t qp = sm + 6 * K2_STAGE + hd * 8192 + r0 * 16 + t * 4, qa = qp + (hd ? 4096 : 0), qb = qp + (hd ? 0 : 4096);
    if (!QSM) { q[0] = lds32(qa); q[1] = lds32(qa + 128); q[2] = lds32(qa + 2048); q[3] = lds32(qa + 2176); }
    q[4] = lds32(qb); q[5] = lds32(qb + 128); q[6] = lds32(qb + 2048); q[7] = lds32(qb + 2176);
  }
  if (first && warp != 7) named_arrive(6, 512);
  const int zero = kid >> 16;
  const uint32_t k0 = __shfl_sync(~0u, dlo(sm + hd * 20480, 2048) + (lane & zero), 0), v0 = __shfl_sync(~0u, dlo(sm + hd * 16384 + 8192, 128) + (lane & zero), 0);
  const uint32_t qlo = QSM ? __shfl_sync(~0u, dlo(sm + 6 * K2_STAGE + hd * 12288 + rh * 1024, 2048) + (lane & zero), 0) : 0u;
  const bool padl = hd && t == 0, padh = !hd && t == 2;
  const int lsrc = (lane & ~3) | (hd ? 0 : 2);
  float o[16];
  uint32_t sa[32], sb[32], oh[8];
  const uint32_t ilo = __shfl_sync(~0u, dlo(aux + 1792, 128) + (lane & zero), 0);
#pragma unroll
  for (int i = 0; i < 16; i++) o[i] = 0.f;
  reg_fence(o);
  qk128<QSM>(sa, qlo, q, k0, KQ_HI + zero);
  wg_wait<0>();
  reg_fence(sa);
  {
    uint32_t m0 = sa[0], m1 = sa[1];
#pragma unroll
    for (int c = 1; c < 16; c++) { m0 = hmax2(m0, sa[2 * c]); m1 = hmax2(m1, sa[2 * c + 1]); }
    uint32_t mm = hmax2(__byte_perm(m0, m1, 0x5410), __byte_perm(m0, m1, 0x7632));
    mm = hmax2(mm, __shfl_xor_sync(~0u, mm, 1)); mm = hmax2(mm, __shfl_xor_sync(~0u, mm, 2));
    asm("sub.rn.f16x2 %0, %1, %0;" : "+r"(mm) : "r"(0x44004400u));
    if (padl) { q[4] = mm & 0xFFFFu; q[5] = mm >> 16; }
    if (padh) { q[6] = mm & 0xFFFFu; q[7] = mm >> 16; }
#pragma unroll
    for (int i = QSM ? 4 : 0; i < 8; i++) asm volatile("" : "+r"(q[i])::"memory");
    m0 = __byte_perm(mm, mm, 0x1010); m1 = __byte_perm(mm, mm, 0x3232);
#pragma unroll
    for (int c = 0; c < 16; c++) {
      asm("add.rn.f16x2 %0, %0, %1;" : "+r"(sa[2 * c]) : "r"(m0));
      asm("add.rn.f16x2 %0, %0, %1;" : "+r"(sa[2 * c + 1]) : "r"(m1));
    }
  }
  uint32_t duty = warp == 7 ? 0x11u : warp == 11 ? 0x0Cu : warp == 15 ? 0x22u : 0u;
  duty = __shfl_sync(~0u, duty + (lane & zero), 0);
  uint32_t rel = (tid & 127) == 0 ? bars + 64 : 0u;
  asm volatile("" : "+r"(rel));
  uint32_t lo = 0x662F662Fu;
  sm_pv<0, true>(oh, sa, lo, ovf, zero, v0);
  mbar_wait(bars, 0);
  wg_wait<0>();
  qk128<QSM>(sb, qlo, q, k0 + (K2_STAGE >> 4), KQ_HI + zero);
  wg_wait<0>();
  int slot = 0, ph = 0;
#pragma unroll 1
  for (int p = 0;; p++) {
    const int nxt = slot == 2 ? 0 : slot + 1, prv = slot == 0 ? 2 : slot - 1;
    const uint32_t v1 = v0 + slot * (K2_STAGE >> 3) + (K2_STAGE >> 4), offn = nxt * (K2_STAGE >> 3), v2 = v0 + offn;
    if (nxt == 0) ph ^= 1;
    reg_fence(sb);
    softmax_h<0, 8>(sb, lo, ovf, zero);
    if (p < 7) mbar_wait(bars + nxt * 8, ph);
    wg_wait<0>();
    qk128<QSM>(sa, qlo, q, k0 + offn, KQ_HI + zero);
    if ((duty >> p) & 1) {
      const int c = __shfl_sync(~0u, cta + (p & zero), 0);
      if (p > 0) mbar_wait(bars + 64 + prv * 8, p > 3);
      if (elect_one())
        kv_load(sm + prv * 2 * K2_STAGE, bars + prv * 8, g_qkv + (MAP_J(c) * 8 + ((MAP_TB(c) >> 1) <= p + 1 ? p + 2 : p + 1)) * 32768, 2 * K2_STAGE);
      if (first && slot != 1) {
        if (p == 0) named_bar(6, 512);
        repack_step(P, sm + K2_ST * K2_STAGE, bars + 96, (p * 2 + 1) / 3, c);
      }
      __syncwarp();
    }
    softmax_h<8, 16>(sb, lo, ovf, zero);
    pv128h<0, 4, false>(oh, sb, v1, V_HI | (v1 & zero));
    softmax_h<16, 32>(sb, lo, ovf, zero);
    pv128h<4, 8, false>(oh, sb, v1, V_HI | (v1 & zero));
    if (p == 7) break;
    wg_wait<2>();
    reg_fence(sa);
    softmax_h<0, 8>(sa, lo, ovf, zero);
    wg_wait<0>();
    reg_fence(oh);
    o_fold(o, oh, ilo);
    qk128<QSM>(sb, qlo, q, k0 + offn + (K2_STAGE >> 4), KQ_HI + zero);
    if (rel) mbar_arrive(rel + slot * 8);
    softmax_h<8, 16>(sa, lo, ovf, zero);
    pv128h<0, 4, true>(oh, sa, v2, V_HI | (v2 & zero));
    softmax_h<16, 32>(sa, lo, ovf, zero);
    pv128h<4, 8, false>(oh, sa, v2, V_HI | (v2 & zero));
    slot = nxt;
  }
  wg_wait<0>();
  reg_fence(oh);
  o_fold(o, oh, ilo);
  wg_wait<0>();
  reg_fence(o); reg_fence(sa);
#pragma unroll
  for (int i = 0; i < 8; i++) { const float x = o[i]; o[i] = o[12 - (i & 4) * 2 + (i & 4) + (i & 3)]; o[12 - (i & 4) * 2 + (i & 4) + (i & 3)] = x; }
  float l0 = __shfl_sync(~0u, hd ? o[0] : o[12], lsrc), l1 = __shfl_sync(~0u, hd ? o[2] : o[14], lsrc);
  float big = 0.f;
#pragma unroll
  for (int i = 0; i < 16; i++) big += o[i] * 0.f;
  const bool bad = !(big == 0.f) || !(l0 > 0.f) || !(l1 > 0.f) || (ovf & ~0x663F663Fu);
  uint32_t* op = reinterpret_cast<uint32_t*>(g_ot + (size_t)(tb * 8 + m) * BLK) + hd * 1536 + r0 * 4 + t;
  auto store_o = [&]() {
    const float i0 = __fdividef(1.0f, l0), i1 = __fdividef(1.0f, l1);
#pragma unroll
    for (int c = 0; c < 4; c++) {
      if (hd ? (c > 0 || t >= 2) : (c < 3 || t < 2)) {
        op[c * 512] = pack_bf16(o[4 * c] * i0, o[4 * c + 1] * i0);
        op[c * 512 + 32] = pack_bf16(o[4 * c + 2] * i1, o[4 * c + 3] * i1);
      }
    }
  };
  store_o();
  if (__syncthreads_or(bad)) {
    if (padl) { q[4] = 0u; q[5] = 0u; }
    if (padh) { q[6] = 0u; q[7] = 0u; }
    float m0 = -INFINITY, m1 = -INFINITY, sf[32];
#pragma unroll
    for (int i = 0; i < 32; i++) sa[i] = 0u;
#pragma unroll
    for (int i = 0; i < 16; i++) o[i] = 0.f;
#pragma unroll
    for (int i = 0; i < 32; i++) sf[i] = 0.f;
#pragma unroll 1
    for (int i2 = 0; i2 < 32; i2++) {
      if ((i2 & 1) == 0) {
        __syncthreads();
        if (tid == 0) kv_load(sm, bars + 24, kv + (i2 >> 1) * 16384, K2_STAGE);
        mbar_wait(bars + 24, ((i2 >> 1) + 1) & 1);
      }
      const uint32_t kl = k0 + (i2 & 1) * 64;
      reg_fence(sf);
#pragma unroll
      for (int i = QSM ? 4 : 0; i < 8; i++) asm volatile("" : "+r"(q[i])::"memory");
      wg_fence();
      if (QSM) wgmma_sf_n64<0>(sf, desc64(qlo, KQ_HI), desc64(kl, KQ_HI), zero);
      else wgmma_rf_n64<0>(sf, q[0], q[1], q[2], q[3], desc64(kl, KQ_HI), zero);
      wgmma_rf_n64<0>(sf, q[4], q[5], q[6], q[7], desc64(kl ^ 256, KQ_HI), 1);
      wg_commit();
      wg_wait<0>();
      reg_fence(sf);
      float n0, n1;
      rowmax64(sf, n0, n1);
      n0 = fmaxf(n0, m0); n1 = fmaxf(n1, m1);
      const float c0 = ex2(m0 - n0), c1 = ex2(m1 - n1);
      m0 = n0; m1 = n1;
#pragma unroll
      for (int c = 0; c < 4; c++) { o[4 * c] *= c0; o[4 * c + 1] *= c0; o[4 * c + 2] *= c1; o[4 * c + 3] *= c1; }
#pragma unroll
      for (int c = 0; c < 8; c++) {
        sa[2 * c] = pack_f16(ex2(sf[4 * c] - m0 + 12.f), ex2(sf[4 * c + 1] - m0 + 12.f));
        sa[2 * c + 1] = pack_f16(ex2(sf[4 * c + 2] - m1 + 12.f), ex2(sf[4 * c + 3] - m1 + 12.f));
      }
      reg_fence(sa); reg_fence(o);
      pv128<0, 4>(o, sa, v0 + (i2 & 1) * 64, V_HI);
      wg_wait<0>();
      reg_fence(o);
    }
    l0 = __shfl_sync(~0u, hd ? o[0] : o[12], lsrc); l1 = __shfl_sync(~0u, hd ? o[2] : o[14], lsrc);
    store_o();
  }
  if (warp == 15 && elect_one()) asm volatile("cp.async.bulk.wait_group.read 0;" ::: "memory");
}

typedef CUresult (*EncFn)(CUtensorMap*, CUtensorMapDataType, cuuint32_t, void*, const cuuint64_t*, const cuuint64_t*, const cuuint32_t*,
                          const cuuint32_t*, CUtensorMapInterleave, CUtensorMapSwizzle, CUtensorMapL2promotion, CUtensorMapFloatOOBfill);
static EncFn enc_fn() {
  static EncFn fn = nullptr;
  if (!fn) { cudaDriverEntryPointQueryResult q; cudaGetDriverEntryPoint("cuTensorMapEncodeTiled", (void**)&fn, cudaEnableDefault, &q); }
  return fn;
}
static CUtensorMap map2d(const void* p, int cols, int rows, int bc, int br, CUtensorMapSwizzle sw) {
  CUtensorMap m; cuuint64_t gd[2] = {(cuuint64_t)cols, (cuuint64_t)rows}, gs[1] = {(cuuint64_t)cols * 2};
  cuuint32_t bd[2] = {(cuuint32_t)bc, (cuuint32_t)br}, es[2] = {1, 1};
  enc_fn()(&m, CU_TENSOR_MAP_DATA_TYPE_BFLOAT16, 2, (void*)p, gd, gs, bd, es, CU_TENSOR_MAP_INTERLEAVE_NONE, sw,
           CU_TENSOR_MAP_L2_PROMOTION_L2_128B, CU_TENSOR_MAP_FLOAT_OOB_FILL_NONE);
  return m;
}
static CUtensorMap mapg(const void* p, int cols, int rows, int r0, int br, int bg) {
  CUtensorMap m; const int nd = r0 ? 4 : 3;
  cuuint64_t gd[4], gs[3]; cuuint32_t bd[4], es[4] = {1, 1, 1, 1};
  gd[0] = 8; bd[0] = 8; gd[1] = r0 ? r0 : rows; bd[1] = br; gs[0] = (cuuint64_t)cols * 2;
  if (r0) { gd[2] = rows / r0; bd[2] = 2; gs[1] = (cuuint64_t)r0 * cols * 2; }
  gd[nd - 1] = cols / 8; bd[nd - 1] = bg; gs[nd - 2] = 16;
  enc_fn()(&m, CU_TENSOR_MAP_DATA_TYPE_BFLOAT16, nd, (void*)p, gd, gs, bd, es, CU_TENSOR_MAP_INTERLEAVE_NONE, CU_TENSOR_MAP_SWIZZLE_NONE,
           CU_TENSOR_MAP_L2_PROMOTION_L2_128B, CU_TENSOR_MAP_FLOAT_OOB_FILL_NONE);
  return m;
}
template <class... KA, class... A>
static void launch(void (*k)(KA...), int grid, int block, int smem, bool pdl, A... a) {
  cudaLaunchConfig_t cfg = {};
  cfg.gridDim = dim3(grid); cfg.blockDim = dim3(block); cfg.dynamicSmemBytes = smem; cfg.stream = cudaStreamPerThread;
  cudaLaunchAttribute at[1];
  at[0].id = cudaLaunchAttributeProgrammaticStreamSerialization; at[0].val.programmaticStreamSerializationAllowed = 1;
  cfg.attrs = at; cfg.numAttrs = pdl ? 1 : 0;
  cudaLaunchKernelEx(&cfg, k, KA(a)...);
}

extern "C" void kernel_launch(void* const* d_in, const int* in_sizes, int n_in, void* d_out, int out_size) {
  const bf16* x0 = (const bf16*)d_in[0];
  const bf16* wqkv = (const bf16*)d_in[1];
  const bf16* wo = (const bf16*)d_in[2];
  const bf16* wg = (const bf16*)d_in[4];
  const bf16* wu = (const bf16*)d_in[5];
  const bf16* wd = (const bf16*)d_in[6];
  bf16* out = (bf16*)d_out;
  const Weights W = {wg, wu};
  cudaFuncSetAttribute(k2_attn<false>, cudaFuncAttributeMaxDynamicSharedMemorySize, K2_SMEM);
  cudaFuncSetAttribute(k2_attn<true>, cudaFuncAttributeMaxDynamicSharedMemorySize, K2_SMEM);
  cudaFuncSetAttribute(k_wo<false>, cudaFuncAttributeMaxDynamicSharedMemorySize, WO_SMEM);
  cudaFuncSetAttribute(k_wo<true>, cudaFuncAttributeMaxDynamicSharedMemorySize, WO_SMEM);
  cudaFuncSetAttribute(k_chain<false>, cudaFuncAttributeMaxDynamicSharedMemorySize, CH_SMEM);
  cudaFuncSetAttribute(k_chain<true>, cudaFuncAttributeMaxDynamicSharedMemorySize, CH_SMEM);
  CUtensorMap mout = map2d(out, D_, S_, 56, 128, CU_TENSOR_MAP_SWIZZLE_NONE);
  CUtensorMap mres = map2d(x0, D_, S_, 56, 128, CU_TENSOR_MAP_SWIZZLE_NONE);
  PackMaps P;
  P.g = mapg(wg, F_, D_, 0, 64, 7); P.u = mapg(wu, F_, D_, 0, 64, 7); P.d = mapg(wd, D_, F_, 224, 56, 7);
  P.o = mapg(wo, D_, D_, 0, 112, 7); P.q = mapg(wqkv, NQ_, D_, 0, 64, 7);
  P.xa = map2d(x0, D_, S_, 64, 128, CU_TENSOR_MAP_SWIZZLE_128B); P.wb = map2d(wqkv, NQ_, D_, 56, 64, CU_TENSOR_MAP_SWIZZLE_128B);

  int nsm = 0;
  cudaDeviceGetAttribute(&nsm, cudaDevAttrMultiProcessorCount, 0);
  launch(k2_attn<true>, 128, 512, K2_SMEM, false, P, 0);
  launch(k_wo<false>, nsm, 288, WO_SMEM, true, mres, W, 7);
  launch(k_chain<false>, nsm, C2_THREADS, CH_SMEM, true, mout, 3);
  launch(k2_attn<false>, nsm, 512, K2_SMEM, true, P, 5);
  launch(k_wo<true>, nsm, 288, WO_SMEM, true, mres, W, 8);
  launch(k_chain<true>, nsm, C2_THREADS, CH_SMEM, true, mout, 6);
}
```
